```python
import torch

def _softmax(x, axis=-1):
    return torch.softmax(x, dim=axis)
def _gelu(x):
    return torch.nn.functional.gelu(x, approximate="tanh")
def _silu(x):
    return torch.nn.functional.silu(x)
def _sigmoid(x):
    return torch.sigmoid(x)
def _layernorm(x, axis=-1, eps=1e-5):
    m = x.mean(dim=axis, keepdim=True)
    v = x.var(dim=axis, keepdim=True, unbiased=False)
    return (x - m) / torch.sqrt(v + eps)
def _scatter_add(tgt, idx, src, axis=0):
    return tgt.clone().index_add_(axis, idx, src)
def _segment_sum(src, seg, n):
    out = torch.zeros((n,) + src.shape[1:], dtype=src.dtype)
    return out.index_add_(0, seg, src)
def _pad(x, pw):
    flat = tuple(v for pair in reversed(pw) for v in pair)
    return torch.nn.functional.pad(x, flat)

kernel_name = 'standalone__deep_cross_fibinet__recsys'

def setup_inputs():

    _w = (lambda a: (lambda t: t.to(torch.bfloat16) if t.is_floating_point() else t)(torch.as_tensor(a)))
    B, F, D = 4096, 26, 128
    V = min(1000000, 100000)
    Fr = max(F // 2, 1)
    H = min(F * D, 256)
    return {
        "idx": _w((lambda lo, hi, *s: torch.randint(lo, hi, s))(0, V, B, F).to(torch.int64)),
        "table": _w((lambda *s: torch.randn(*s, dtype=torch.bfloat16) * 1.6)(V, D)),
        "se_w1": _w((lambda *s: torch.randn(*s, dtype=torch.bfloat16) * 1.6)(F, Fr)),
        "se_w2": _w((lambda *s: torch.randn(*s, dtype=torch.bfloat16) * 1.6)(Fr, F)),
        "w_bi": _w((lambda *s: torch.randn(*s, dtype=torch.bfloat16) * 0.05)(D, D) * (D ** -0.5)),
        "w_cross": _w((lambda *s: torch.randn(*s, dtype=torch.bfloat16) * 0.05)(2 * F * F * D) * 0.01),
        "w_deep1": _w((lambda *s: torch.randn(*s, dtype=torch.bfloat16) * 0.8)(F * D, H) * ((F * D) ** -0.5)),
        "w_deep2": _w((lambda *s: torch.randn(*s, dtype=torch.bfloat16) * 0.05)(H) * 0.01),
    }

def reference(idx, table, se_w1, se_w2, w_bi, w_cross, w_deep1, w_deep2):
    emb = table[idx]
    B = emb.shape[0]
    z = emb.mean(axis=-1)
    a = _sigmoid(_gelu(z @ se_w1) @ se_w2)
    v = a[:, :, None] * emb
    eW = torch.einsum('bfd,de->bfe', emb, w_bi)
    vW = torch.einsum('bfd,de->bfe', v, w_bi)
    p = torch.einsum('bie,bje->bije', eW, emb).reshape(B, -1)
    q = torch.einsum('bie,bje->bije', vW, v).reshape(B, -1)
    cross_feat = torch.concatenate([p, q], axis=-1)
    logit_cross = cross_feat @ w_cross
    h = _gelu(emb.reshape(B, -1) @ w_deep1)
    logit_deep = h @ w_deep2
    return logit_cross + logit_deep
```

```cpp
#include <cuda_runtime.h>
#include <cuda_bf16.h>
#include <cuda.h>
#include <stdint.h>

#define STAMP(k) do { } while (0)

#define KDB 16
constexpr uint32_t S_TILE   = 4224;
constexpr uint32_t OFF_L    = 0;
constexpr uint32_t OFF_BAR  = 26 * S_TILE;
constexpr uint32_t OFF_P0   = 110592;
constexpr uint32_t OFF_PEER = OFF_P0 + 6 * 16384;
constexpr uint32_t OFF_IDX  = OFF_PEER + 3 * 4096;
constexpr uint32_t OFF_ZL   = OFF_IDX + 3328;
constexpr uint32_t OFF_ZP   = OFF_ZL + 3328;
constexpr uint32_t OFF_RED  = OFF_ZP + 3328;
constexpr uint32_t OFF_ZERO = OFF_RED + 512;
constexpr uint32_t SMEM_BYTES = OFF_ZERO + 128;
constexpr uint32_t OFF_A   = OFF_P0;
constexpr uint32_t OFF_B   = OFF_A + 8 * S_TILE;
constexpr uint32_t OFF_SCR = OFF_B + 8 * S_TILE;
constexpr uint32_t OFF_JIT = OFF_SCR + 24576;
constexpr uint32_t OFF_X   = OFF_SCR + 32768;
constexpr uint32_t OFF_AV  = OFF_X + 2 * S_TILE;
constexpr uint32_t WC_STAGE = 7168;
static_assert(OFF_AV + 32 * 14 * 4 <= OFF_IDX, "a-values overlap");
static_assert(OFF_B + 8 * WC_STAGE <= OFF_JIT, "ring overlap");
static_assert(SMEM_BYTES <= 232448, "smem");

enum {
    B_W1F = 0, B_W1E = 6, B_AF = 12, B_AE = 38, B_RF = 41, B_GD = 49, B_SD = 57, B_WCF = 58, B_WCE = 66,
    B_HX = 74, B_ZX = 75, B_ZL = 76, B_RDY = 77, B_AOK = 78, B_PREP = 79, B_FR = 80, B_TD = 83, B_SB = 85, B_COUNT = 86
};

__device__ uint4 g_wc[64 * WC_STAGE / 16 + 64];
__device__ uint4 g_wt[2 * 8 * 128];
__device__ unsigned g_cnt;

__device__ __forceinline__ uint32_t smem_u32(const void* p) { return (uint32_t)__cvta_generic_to_shared(p); }
__device__ __forceinline__ void mbar_init(uint32_t a, uint32_t c) { asm volatile("mbarrier.init.shared::cta.b64 [%0], %1;" ::"r"(a), "r"(c)); }
__device__ __forceinline__ void mbar_expect(uint32_t a, uint32_t b) { asm volatile("mbarrier.arrive.expect_tx.shared::cta.b64 _, [%0], %1;" ::"r"(a), "r"(b) : "memory"); }
__device__ __forceinline__ void mbar_arrive(uint32_t a) { asm volatile("mbarrier.arrive.shared::cta.b64 _, [%0];" ::"r"(a) : "memory"); }
__device__ __forceinline__ uint32_t mbar_test(uint32_t a, uint32_t p) {
    uint32_t done;
    asm volatile("{.reg .pred P; mbarrier.test_wait.parity.shared::cta.b64 P,[%1],%2; selp.u32 %0,1,0,P;}" : "=r"(done) : "r"(a), "r"(p) : "memory");
    return done;
}
__device__ __forceinline__ void mbar_wait(uint32_t a, uint32_t p) {
    asm volatile("{.reg .pred P, Q; .reg .u32 it;\n\t"
                 "mov.u32 it, 0;\n\t"
                 "WL: mbarrier.try_wait.parity.shared::cta.b64 P,[%0],%1;\n\t"
                 "add.u32 it, it, 1;\n\t"
                 "setp.lt.and.u32 Q, it, 100000, !P;\n\t"
                 "@Q bra WL;\n\t"
                 "}" ::"r"(a), "r"(p) : "memory");
}
__device__ __forceinline__ void mbar_wait_cluster(uint32_t a, uint32_t p) {
    asm volatile("{.reg .pred P, Q; .reg .u32 it;\n\t"
                 "mov.u32 it, 0;\n\t"
                 "WL: mbarrier.try_wait.parity.acquire.cluster.shared::cta.b64 P,[%0],%1;\n\t"
                 "add.u32 it, it, 1;\n\t"
                 "setp.lt.and.u32 Q, it, 100000, !P;\n\t"
                 "@Q bra WL;\n\t"
                 "}" ::"r"(a), "r"(p) : "memory");
}
__device__ __forceinline__ void cpasync16(uint32_t dst, const void* src) { asm volatile("cp.async.cg.shared.global [%0],[%1],16;" ::"r"(dst), "l"(src) : "memory"); }
__device__ __forceinline__ void cpasync16_pf(uint32_t dst, const void* src) { asm volatile("cp.async.cg.shared.global.L2::256B [%0],[%1],16;" ::"r"(dst), "l"(src) : "memory"); }
__device__ __forceinline__ void cpasync_arrive(uint32_t bar) { asm volatile("cp.async.mbarrier.arrive.noinc.shared::cta.b64 [%0];" ::"r"(bar) : "memory"); }
__device__ __forceinline__ uint32_t swz(uint32_t a) { return a ^ ((a >> 3) & 0x70); }
__device__ __forceinline__ void ldsm4(uint32_t* r, uint32_t a) {
    asm volatile("ldmatrix.sync.aligned.m8n8.x4.shared.b16 {%0,%1,%2,%3},[%4];" : "=r"(r[0]), "=r"(r[1]), "=r"(r[2]), "=r"(r[3]) : "r"(a) : "memory");
}
__device__ __forceinline__ void ldsm2t(uint32_t& r0, uint32_t& r1, uint32_t a) {
    asm volatile("ldmatrix.sync.aligned.m8n8.x2.trans.shared.b16 {%0,%1},[%2];" : "=r"(r0), "=r"(r1) : "r"(a) : "memory");
}
__device__ __forceinline__ void ldsm4t(uint32_t* r, uint32_t a) {
    asm volatile("ldmatrix.sync.aligned.m8n8.x4.trans.shared.b16 {%0,%1,%2,%3},[%4];" : "=r"(r[0]), "=r"(r[1]), "=r"(r[2]), "=r"(r[3]) : "r"(a) : "memory");
}
__device__ __forceinline__ void stsm4(uint32_t a, uint32_t r0, uint32_t r1, uint32_t r2, uint32_t r3) {
    asm volatile("stmatrix.sync.aligned.m8n8.x4.shared.b16 [%0],{%1,%2,%3,%4};" ::"r"(a), "r"(r0), "r"(r1), "r"(r2), "r"(r3) : "memory");
}
__device__ __forceinline__ void lds128(uint32_t* r, uint32_t a) {
    asm volatile("ld.shared.v4.u32 {%0,%1,%2,%3},[%4];" : "=r"(r[0]), "=r"(r[1]), "=r"(r[2]), "=r"(r[3]) : "r"(a) : "memory");
}
__device__ __forceinline__ uint32_t lds32(uint32_t a) { uint32_t r; asm volatile("ld.shared.u32 %0,[%1];" : "=r"(r) : "r"(a) : "memory"); return r; }
__device__ __forceinline__ void sts32(uint32_t a, uint32_t v) { asm volatile("st.shared.u32 [%0],%1;" ::"r"(a), "r"(v) : "memory"); }
__device__ __forceinline__ uint32_t pack_bf16(float lo, float hi) { uint32_t r; asm("cvt.rn.bf16x2.f32 %0,%1,%2;" : "=r"(r) : "f"(hi), "f"(lo)); return r; }
__device__ __forceinline__ uint32_t mul_bf16x2(uint32_t a, uint32_t b) { uint32_t r; asm volatile("mul.rn.bf16x2 %0,%1,%2;" : "=r"(r) : "r"(a), "r"(b)); return r; }
__device__ __forceinline__ uint32_t vxor(uint32_t a, uint32_t b) { uint32_t r; asm volatile("xor.b32 %0,%1,%2;" : "=r"(r) : "r"(a), "r"(b)); return r; }
__device__ __forceinline__ float bf_lo(uint32_t x) { return __uint_as_float(x << 16); }
__device__ __forceinline__ float bf_hi(uint32_t x) { return __uint_as_float(x & 0xffff0000u); }
__device__ __forceinline__ float bfr(float x) { return __bfloat162float(__float2bfloat16_rn(x)); }
__device__ __forceinline__ float tanh_fast(float u) { float t; asm("tanh.approx.f32 %0,%1;" : "=f"(t) : "f"(u)); return t; }
__device__ __forceinline__ void wg_fence() { asm volatile("wgmma.fence.sync.aligned;" ::: "memory"); }
__device__ __forceinline__ void wg_commit() { asm volatile("wgmma.commit_group.sync.aligned;" ::: "memory"); }
template <int N> __device__ __forceinline__ void wg_wait() { asm volatile("wgmma.wait_group.sync.aligned %0;" ::"n"(N) : "memory"); }
template <int N> __device__ __forceinline__ void fence_regs(float* d) {
#pragma unroll
    for (int i = 0; i < N; i++) asm volatile("" : "+f"(d[i])::"memory");
}
__device__ __forceinline__ uint32_t uni(uint32_t x) { return __shfl_sync(0xffffffffu, x, 0); }
__device__ __forceinline__ void fence_async() { asm volatile("fence.proxy.async.shared::cta;" ::: "memory"); }
__device__ __forceinline__ uint64_t mk64(uint32_t lo, uint32_t hi) { return ((uint64_t)hi << 32) | lo; }

#define D8(b) "+f"(d[b + 0]), "+f"(d[b + 1]), "+f"(d[b + 2]), "+f"(d[b + 3]), "+f"(d[b + 4]), "+f"(d[b + 5]), "+f"(d[b + 6]), "+f"(d[b + 7])
#define O8(b) "=f"(d[b + 0]), "=f"(d[b + 1]), "=f"(d[b + 2]), "=f"(d[b + 3]), "=f"(d[b + 4]), "=f"(d[b + 5]), "=f"(d[b + 6]), "=f"(d[b + 7])
#define L16 "{%0,%1,%2,%3,%4,%5,%6,%7,%8,%9,%10,%11,%12,%13,%14,%15}"
#define L32 "{%0,%1,%2,%3,%4,%5,%6,%7,%8,%9,%10,%11,%12,%13,%14,%15,%16,%17,%18,%19,%20,%21,%22,%23,%24,%25,%26,%27,%28,%29,%30,%31}"
#define L64 "{%0,%1,%2,%3,%4,%5,%6,%7,%8,%9,%10,%11,%12,%13,%14,%15,%16,%17,%18,%19,%20,%21,%22,%23,%24,%25,%26,%27,%28,%29,%30,%31,%32,%33,%34,%35,%36,%37,%38,%39,%40,%41,%42,%43,%44,%45,%46,%47,%48,%49,%50,%51,%52,%53,%54,%55,%56,%57,%58,%59,%60,%61,%62,%63}"

#define DSC_PRE(B, O, H) "{.reg .b32 lo; .reg .b64 dsc; add.u32 lo, " B ", " O "; mov.b64 dsc, {lo, " H "}; "
template <uint32_t OFF, uint32_t HI> __device__ __forceinline__ void wg128_tb(float* d, const uint32_t* a, uint32_t base) {
    asm volatile(DSC_PRE("%68", "%69", "%70") "wgmma.mma_async.sync.aligned.m64n128k16.f32.bf16.bf16 " L64 ", {%64,%65,%66,%67}, dsc, 1,1,1,1;}"
                 : D8(0), D8(8), D8(16), D8(24), D8(32), D8(40), D8(48), D8(56)
                 : "r"(a[0]), "r"(a[1]), "r"(a[2]), "r"(a[3]), "r"(base), "n"(OFF), "n"(HI));
}
template <bool ACC, uint32_t OFF, uint32_t HI> __device__ __forceinline__ void wg64(float* d, const uint32_t* a, uint32_t base) {
    if (ACC)
        asm volatile(DSC_PRE("%36", "%37", "%38") "wgmma.mma_async.sync.aligned.m64n64k16.f32.bf16.bf16 " L32 ", {%32,%33,%34,%35}, dsc, 1,1,1,0;}"
                     : D8(0), D8(8), D8(16), D8(24) : "r"(a[0]), "r"(a[1]), "r"(a[2]), "r"(a[3]), "r"(base), "n"(OFF), "n"(HI));
    else
        asm volatile(DSC_PRE("%36", "%37", "%38") "wgmma.mma_async.sync.aligned.m64n64k16.f32.bf16.bf16 " L32 ", {%32,%33,%34,%35}, dsc, 0,1,1,0;}"
                     : O8(0), O8(8), O8(16), O8(24) : "r"(a[0]), "r"(a[1]), "r"(a[2]), "r"(a[3]), "r"(base), "n"(OFF), "n"(HI));
}
template <bool ACC, uint32_t OFF, uint32_t HI> __device__ __forceinline__ void wg32(float* d, const uint32_t* a, uint32_t base) {
    if (ACC)
        asm volatile(DSC_PRE("%20", "%21", "%22") "wgmma.mma_async.sync.aligned.m64n32k16.f32.bf16.bf16 " L16 ", {%16,%17,%18,%19}, dsc, 1,1,1,0;}"
                     : D8(0), D8(8) : "r"(a[0]), "r"(a[1]), "r"(a[2]), "r"(a[3]), "r"(base), "n"(OFF), "n"(HI));
    else
        asm volatile(DSC_PRE("%20", "%21", "%22") "wgmma.mma_async.sync.aligned.m64n32k16.f32.bf16.bf16 " L16 ", {%16,%17,%18,%19}, dsc, 0,1,1,0;}"
                     : O8(0), O8(8) : "r"(a[0]), "r"(a[1]), "r"(a[2]), "r"(a[3]), "r"(base), "n"(OFF), "n"(HI));
}
template <bool ACC, uint32_t OFF, uint32_t HI>
__device__ __forceinline__ void wgsp32(float* d, uint32_t a0, uint32_t a1, uint32_t a2, uint32_t a3, uint32_t base, uint32_t meta) {
    if (ACC)
        asm volatile(DSC_PRE("%20", "%22", "%23") "wgmma.mma_async.sp.sync.aligned.m64n32k32.f32.bf16.bf16 " L16 ", {%16,%17,%18,%19}, dsc, %21, 0, 1,1,1,0;}"
                     : D8(0), D8(8) : "r"(a0), "r"(a1), "r"(a2), "r"(a3), "r"(base), "r"(meta), "n"(OFF), "n"(HI));
    else
        asm volatile(DSC_PRE("%20", "%22", "%23") "wgmma.mma_async.sp.sync.aligned.m64n32k32.f32.bf16.bf16 " L16 ", {%16,%17,%18,%19}, dsc, %21, 0, 0,1,1,0;}"
                     : O8(0), O8(8) : "r"(a0), "r"(a1), "r"(a2), "r"(a3), "r"(base), "r"(meta), "n"(OFF), "n"(HI));
}
__device__ __forceinline__ void mma16816(float* c, const uint32_t* a, uint32_t b0, uint32_t b1) {
    asm volatile("mma.sync.aligned.m16n8k16.row.col.f32.bf16.bf16.f32 {%0,%1,%2,%3},{%4,%5,%6,%7},{%8,%9},{%0,%1,%2,%3};"
                 : "+f"(c[0]), "+f"(c[1]), "+f"(c[2]), "+f"(c[3]) : "r"(a[0]), "r"(a[1]), "r"(a[2]), "r"(a[3]), "r"(b0), "r"(b1));
}

__host__ __device__ constexpr uint32_t w1_off(int j, int g) { return OFF_P0 + ((j + 1) % 3) * 32768 + g * 16384; }

template <bool PF>
__device__ __forceinline__ void gather_tile(uint32_t dst_tile, const uint32_t* off8, const char* tb, int lane) {
    const uint32_t x = dst_tile + (lane >> 3) * 128 + (lane & 7) * 16;
    const uint32_t x0 = swz(x), x1 = swz(x + 512);
#pragma unroll
    for (int i = 0; i < 8; i++) {
        const uint32_t dst = ((i & 1) ? x1 : x0) + (i >> 1) * 1024;
        if (PF) cpasync16_pf(dst, tb + off8[i]); else cpasync16(dst, tb + off8[i]);
    }
}

struct Ctx {
    uint32_t sb, bar;
    int wg, w, lane;
    long long t_start;
};

template <int WAVE, int G, int O>
__device__ __forceinline__ void issue_chain64(float* acc, const uint32_t* wf, uint32_t cb) {
    constexpr uint32_t hi = (S_TILE >> 4) | (1u << 30);
    constexpr uint32_t roff = (G == 0) ? OFF_A : (G == 1) ? OFF_B : (WAVE == 0 ? OFF_A : OFF_L);
    constexpr uint32_t lo0 = (((OFF_L + G * 8 * S_TILE) >> 4) + O * 64) | (1u << 16);
    constexpr uint32_t lo1 = ((roff >> 4) + O * 64) | (1u << 16);
    wg_fence();
    wg64<false, lo0, hi>(acc, wf, cb);
    wg64<true, lo0 + 2, hi>(acc, wf + 4, cb);
    wg64<true, lo0 + 4, hi>(acc, wf + 8, cb);
    wg64<true, lo0 + 6, hi>(acc, wf + 12, cb);
    wg64<true, lo1, hi>(acc, wf + 16, cb);
    wg64<true, lo1 + 2, hi>(acc, wf + 20, cb);
    wg64<true, lo1 + 4, hi>(acc, wf + 24, cb);
    wg64<true, lo1 + 6, hi>(acc, wf + 28, cb);
    wg_commit();
}
__device__ __forceinline__ void store_chain64(const float* acc, uint32_t stb) {
#pragma unroll
    for (int c = 0; c < 8; c += 2)
        stsm4(stb ^ (c << 4), pack_bf16(acc[4 * c], acc[4 * c + 1]), pack_bf16(acc[4 * c + 2], acc[4 * c + 3]),
              pack_bf16(acc[4 * c + 4], acc[4 * c + 5]), pack_bf16(acc[4 * c + 6], acc[4 * c + 7]));
}

template <int WAVE>
__device__ __forceinline__ void wave_body(const Ctx& cx, uint32_t c, float* accA, float* accB, uint32_t* wf, float& logit) {
    const uint32_t sb = cx.sb, bar = uni(cx.bar);
    const int wg = cx.wg;
    int w = cx.w, lane = cx.lane;
    asm volatile("" : "+r"(w), "+r"(lane));
    const bool el = (lane == 0);
    const bool st0 = (threadIdx.x == 0); (void)st0;
    const uint32_t sbm = (sb & 0x3FFFF) >> 4;
    uint32_t H[3][32];
    const int mm = lane >> 3, rr = lane & 7;
    const uint32_t stb = sb + OFF_SCR + (2 * wg) * 8192 + (16 * w + 8 * (mm & 1) + rr) * 128 + (((mm >> 1) ^ rr) << 4);
    const uint32_t ldb = sb + OFF_SCR + w * 8192 + (32 * wg + mm) * 128 + ((rr ^ mm) << 4);
    const uint32_t cb = uni(sbm + wg * 128);
#define EW_STEP(G)                                                                                          \
    {                                                                                                       \
        mbar_wait(bar + 8 * (B_RF + ((G == 2) ? 3 : WAVE * 4 + G + 1)), 0);                                 \
        fence_async();                                                                                      \
        mbar_wait(bar + 8 * B_SB, (WAVE * 4 + G) & 1);                                     \
        wg_wait<1>();                                                                                       \
        fence_regs<32>(accA);                                                                               \
        store_chain64(accA, stb);                                                                           \
        if (G < 2) {                                                                                        \
            issue_chain64<WAVE, (G < 2 ? G + 1 : 0), 0>(accA, wf, cb);                                      \
        } else {                                                                                            \
            constexpr uint32_t hi = (1024 >> 4) | (1u << 30);                                               \
            constexpr uint32_t lo0 = ((OFF_L + 24 * S_TILE) >> 4) | (1u << 16);                             \
            constexpr uint32_t lo1 = (OFF_X >> 4) | (1u << 16);                                             \
            const uint32_t c3 = uni(sbm + wg * (S_TILE >> 4));                                                   \
            wg_fence();                                                                                     \
            wg32<false, lo0, hi>(accA, wf, c3); wg32<true, lo0 + 2, hi>(accA, wf + 4, c3);                  \
            wg32<true, lo0 + 4, hi>(accA, wf + 8, c3); wg32<true, lo0 + 6, hi>(accA, wf + 12, c3);          \
            wg32<true, lo1, hi>(accA, wf + 16, c3); wg32<true, lo1 + 2, hi>(accA, wf + 20, c3);             \
            wg32<true, lo1 + 4, hi>(accA, wf + 24, c3); wg32<true, lo1 + 6, hi>(accA, wf + 28, c3);         \
            wg_commit();                                                                                    \
        }                                                                                                   \
        wg_wait<1>();                                                                                       \
        fence_regs<32>(accB);                                                                               \
        if (el) mbar_arrive(bar + 8 * (B_GD + WAVE * 4 + G));                                               \
        store_chain64(accB, stb + 8192);                                                                    \
        if (G < 2) issue_chain64<WAVE, (G < 2 ? G + 1 : 0), 1>(accB, wf, cb);                               \
        asm volatile("bar.sync 1, 256;" ::: "memory");                                                      \
        if (G < 2) {                                                                                        \
            _Pragma("unroll") for (int k = 0; k < 16; k++)                                                  \
                ldsm2t(H[G][2 * k], H[G][2 * k + 1], (ldb ^ ((2 * k & 6) << 4)) + k * 256);                 \
        } else {                                                                                            \
            _Pragma("unroll") for (int k = 0; k < 8; k++)                                                   \
                ldsm4t(&H[G][4 * k], (ldb ^ ((k & 1) << 6)) + k * 512);                                     \
        }                                                                                                   \
        __syncwarp();                                                                                       \
        if (el) { mbar_arrive(bar + 8 * B_SB); if (WAVE == 0 && G == 2) mbar_arrive(bar + 8 * B_SD); }      \
        if (st0) STAMP(36 + WAVE * 8 + G);                                                                  \
    }
    EW_STEP(0)
    EW_STEP(1)
    EW_STEP(2)
#undef EW_STEP
    wg_wait<0>();
    fence_regs<16>(accA);
    mbar_wait(bar + 8 * B_SB, (WAVE * 4 + 3) & 1);
    {
        const uint32_t jb = sb + OFF_JIT + (mm >> 1) * 2048 + (16 * w + 8 * (mm & 1) + rr) * 32 + wg * 16;
        stsm4(jb, pack_bf16(accA[0], accA[1]), pack_bf16(accA[2], accA[3]), pack_bf16(accA[4], accA[5]), pack_bf16(accA[6], accA[7]));
        stsm4(jb + 4096, pack_bf16(accA[8], accA[9]), pack_bf16(accA[10], accA[11]), pack_bf16(accA[12], accA[13]), pack_bf16(accA[14], accA[15]));
    }
    if (WAVE == 0) mbar_wait(bar + 8 * B_AOK, 0);
    const int g = lane >> 2, t = lane & 3;
    uint32_t ai[4]; float aj[7];
    {
        const uint32_t ab = sb + OFF_AV + (8 * w + g) * 56;
#pragma unroll
        for (int q = 0; q < 3; q++) { ai[q] = lds32(ab + (4 * q + t) * 4); aj[2 * q] = bf_lo(ai[q]); aj[2 * q + 1] = bf_hi(ai[q]); }
        ai[3] = lds32(ab + 48);
        aj[6] = (t & 1) ? bf_hi(ai[3]) : bf_lo(ai[3]);
    }
    constexpr uint32_t PG0 = (WAVE == 0) ? OFF_L : OFF_A;
    constexpr uint32_t PD1 = 8 * S_TILE, PD2 = (WAVE == 0) ? 16 * S_TILE : OFF_L - OFF_A;
    uint32_t pb0, pb1, pb6;
    {
        const uint32_t row = sb + (8 * w + g) * 128;
        pb0 = swz(row + PG0 + (2 * t) * S_TILE) ^ (64 * wg);
        pb1 = swz(row + PG0 + (2 * t + 1) * S_TILE) ^ (64 * wg);
        pb6 = swz(row + (WAVE == 0 ? OFF_L + 24 * S_TILE : OFF_X) + (t & 1) * S_TILE) ^ (64 * wg);
    }
    uint32_t jaddr = (rr < 2) ? sb + OFF_JIT + w * 2048 + (32 * wg + (mm & 1)) * 32 + rr * 16 : sb + OFF_ZERO;
    const uint32_t jinc = (rr < 2) ? 64 : 0;
    asm volatile("bar.sync 1, 256;" ::: "memory");
    constexpr uint32_t ring = ((WAVE == 0 ? OFF_B : OFF_L + 8 * S_TILE) >> 4) | ((512 >> 4) << 16);
    constexpr uint32_t rhi = (128 >> 4);
    const uint32_t rb = uni(sbm + wg * (WC_STAGE >> 4));
    const uint32_t barw = uni(cx.bar + 8 * wg);
    const uint32_t zero = lds32(sb + OFF_ZERO);
    const uint32_t meta = 0xEEEE4444u ^ zero;
    float tp[2][16], tq[2][16];
    uint32_t pr[7][4];
    float s0 = 0.f, s1 = 0.f;
    uint32_t j0, j1, h0, h1, v[8];
#define T_PREP(k)                                                                                   \
    {                                                                                               \
        ldsm2t(j0, j1, jaddr); jaddr += jinc;                                                       \
        v[0] = mul_bf16x2(H[0][2 * (k)], ai[0]); v[1] = mul_bf16x2(H[0][2 * (k) + 1], ai[0]);       \
        v[2] = mul_bf16x2(H[1][2 * (k)], ai[1]); v[3] = mul_bf16x2(H[1][2 * (k) + 1], ai[1]);       \
        v[4] = mul_bf16x2(H[2][2 * (k)], ai[2]); v[5] = mul_bf16x2(H[2][2 * (k) + 1], ai[2]);       \
        h0 = vxor(H[2][2 * (k)], zero); h1 = vxor(H[2][2 * (k) + 1], zero);                                   \
        v[6] = mul_bf16x2(j0, ai[3]); v[7] = mul_bf16x2(j1, ai[3]);                                 \
    }
#define T_ISSUE(k)                                                                                  \
    {                                                                                               \
        mbar_wait(barw + 8 * (B_WCF + 2 * ((k) & 3)), ((k) >> 2) & 1);                      \
        constexpr uint32_t lo = ring + ((k) & 3) * (2 * WC_STAGE >> 4);                             \
        wg_fence();                                                                                 \
        wgsp32<false, lo, rhi>(tp[(k) & 1], H[0][2 * (k)], H[0][2 * (k) + 1], H[1][2 * (k)], H[1][2 * (k) + 1], rb, meta); \
        wgsp32<false, lo + (3584 >> 4), rhi>(tq[(k) & 1], v[0], v[1], v[2], v[3], rb, meta);        \
        wgsp32<true, lo + (2048 >> 4), rhi>(tp[(k) & 1], h0, h1, j0, j1, rb, meta); \
        wgsp32<true, lo + ((3584 + 2048) >> 4), rhi>(tq[(k) & 1], v[4], v[5], v[6], v[7], rb, meta); \
        wg_commit();                                                                                \
    }
#define T_STEP(p)                                                                                   \
    {                                                                                               \
        constexpr int pn = ((p) < 15) ? (p) + 1 : 15;                                               \
        if (((p) & 3) == 0) {                                                                       \
            const uint32_t x0 = pb0 ^ (((p) >> 2) << 4), x1 = pb1 ^ (((p) >> 2) << 4);              \
            lds128(pr[0], x0); lds128(pr[1], x1);                                                   \
            lds128(pr[2], x0 + PD1); lds128(pr[3], x1 + PD1);                                       \
            lds128(pr[4], x0 + PD2); lds128(pr[5], x1 + PD2);                                       \
            lds128(pr[6], pb6 ^ (((p) >> 2) << 4));                                                 \
        }                                                                                           \
        if ((p) >= KDB && (p) < 15) {                                                               \
            T_PREP(pn)                                                                              \
            T_ISSUE(pn)                                                                             \
            wg_wait<1>();                                                                           \
        } else {                                                                                    \
            wg_wait<0>();                                                                           \
        }                                                                                           \
        fence_regs<16>(tp[(p) & 1]); fence_regs<16>(tq[(p) & 1]);                                   \
        if (el) {                                                                                   \
            mbar_arrive(barw + 8 * (B_WCE + 2 * ((p) & 3)));                                \
            if (WAVE == 0 && (p) == 13) mbar_arrive(bar + 8 * B_TD);                                \
            if (WAVE == 0 && (p) == 14) mbar_arrive(bar + 8 * (B_TD + 1));                          \
            if ((p) == 15) mbar_arrive(bar + 8 * B_SB);                                             \
        }                                                                                           \
        if ((p) < KDB && (p) < 15) T_PREP(pn)                                                       \
        const float* P = tp[(p) & 1];                                                               \
        const float* Q = tq[(p) & 1];                                                               \
        _Pragma("unroll") for (int q = 0; q < 7; q++) {                                             \
            const int di = 4 * (q >> 1) + (q & 1);                                                  \
            const uint32_t x = pr[q][(p) & 3];                                                      \
            s0 = fmaf(bf_lo(x), fmaf(aj[q], Q[di], P[di]), s0);                                     \
            s1 = fmaf(bf_hi(x), fmaf(aj[q], Q[di + 2], P[di + 2]), s1);                             \
        }                                                                                           \
        asm volatile("" : "+f"(s0), "+f"(s1));                                                      \
        if ((p) < KDB && (p) < 15) T_ISSUE(pn)                                                      \
        if (WAVE == 0 && (p) == 11) {                          \
            const uint4* src = g_wt + (c ^ 1) * 1024 + (threadIdx.x & 127);                         \
            _Pragma("unroll") for (int s = 0; s < 8; s++) {                                         \
                const uint4 u = __ldcg(src + ((s ^ (4 * c)) << 7));                                 \
                wf[4 * s] = u.x; wf[4 * s + 1] = u.y; wf[4 * s + 2] = u.z; wf[4 * s + 3] = u.w;     \
            }                                                                                       \
        }                                                                                           \
    }
    T_PREP(0)
    T_ISSUE(0)
    T_STEP(0) T_STEP(1) T_STEP(2) T_STEP(3) T_STEP(4) T_STEP(5) T_STEP(6) T_STEP(7)
    T_STEP(8) T_STEP(9) T_STEP(10) T_STEP(11) T_STEP(12) T_STEP(13) T_STEP(14) T_STEP(15)
#undef T_STEP
#undef T_PREP
#undef T_ISSUE
    logit += s0 + s1;
}

__global__ void __cluster_dims__(2, 1, 1) __launch_bounds__(384, 1)
fib_kernel(const __grid_constant__ CUtensorMap tmW1, const int* __restrict__ idx, const char* __restrict__ table,
           const unsigned short* __restrict__ se1, const unsigned short* __restrict__ se2,
           const unsigned short* __restrict__ wbi, const char* __restrict__ wc, const char* __restrict__ w1g,
           const __nv_bfloat16* __restrict__ wd2, __nv_bfloat16* __restrict__ out) {
    extern __shared__ __align__(1024) char sm[];
    const uint32_t sb = smem_u32(sm);
    const uint32_t bar = sb + OFF_BAR;
    const int tid = threadIdx.x, lane = tid & 31;
    const int warp = __shfl_sync(0xffffffffu, tid >> 5, 0);
    uint32_t c; asm("mov.u32 %0, %%cluster_ctarank;" : "=r"(c));
    const int own0 = blockIdx.x * 32, peer0 = (blockIdx.x ^ 1) * 32;

    int pidx = 0;
    if (tid < 208) {
        const int4 v = __ldg((const int4*)(idx + own0 * 26) + tid);
        const int e0 = 4 * tid;
        const int vv[4] = {v.x, v.y, v.z, v.w};
#pragma unroll
        for (int i = 0; i < 4; i++) {
            const int e = e0 + i, b = (e * 2521) >> 16, n = e - 26 * b;
            sts32(sb + OFF_IDX + (n * 32 + (b & 3) * 8 + (b >> 2)) * 4, (uint32_t)vv[i] << 8);
        }
    } else if (tid < 256) {
        for (int i = tid - 208; i < 26 * 8; i += 48) *(uint4*)(sm + OFF_L + (i >> 3) * S_TILE + 4096 + (i & 7) * 16) = make_uint4(0, 0, 0, 0);
        if (tid == 208) *(uint4*)(sm + OFF_ZERO) = make_uint4(0, 0, 0, 0);
    } else if (warp == 8) {
        if (lane == 0) {
#pragma unroll
            for (int i = 0; i < 6; i++) { mbar_init(bar + 8 * (B_W1F + i), 1); mbar_init(bar + 8 * (B_W1E + i), 4); }
            fence_async();
#pragma unroll
            for (int s2 = 0; s2 < 6; s2++) {
                const int g = s2 & 1, s = s2 >> 1;
                mbar_expect(bar + 8 * (B_W1F + g * 3 + s), 16384);
                asm volatile("cp.async.bulk.tensor.3d.shared::cluster.global.mbarrier::complete_tx::bytes [%0],[%1,{%3,%4,%5}],[%2];"
                             ::"r"(sb + w1_off(s, g)), "l"(&tmW1), "r"(bar + 8 * (B_W1F + g * 3 + s)), "r"(0), "r"((int)(s * 128 + c * 64)), "r"(2 * g) : "memory");
            }
        }
    } else if (warp == 9) {
        if (lane == 0) {
#pragma unroll
            for (int i = 0; i < 26; i++) mbar_init(bar + 8 * (B_AF + i), 64);
#pragma unroll
            for (int i = 0; i < 3; i++) { mbar_init(bar + 8 * (B_AE + i), 8); mbar_init(bar + 8 * (B_FR + i), 8); }
        }
    } else if (warp == 10) {
        pidx = __ldg(idx + (peer0 + lane) * 26);
        if (lane == 0) {
#pragma unroll
            for (int i = 0; i < 8; i++) { mbar_init(bar + 8 * (B_RF + i), 64); mbar_init(bar + 8 * (B_GD + i), 8); }
            mbar_init(bar + 8 * B_SD, 8); mbar_init(bar + 8 * B_TD, 8); mbar_init(bar + 8 * (B_TD + 1), 8); mbar_init(bar + 8 * B_SB, 8);
        }
    } else {
        if (lane == 0) {
#pragma unroll
            for (int i = 0; i < 8; i++) { mbar_init(bar + 8 * (B_WCF + i), 1); mbar_init(bar + 8 * (B_WCE + i), 4); }
            mbar_init(bar + 8 * B_HX, 1); mbar_init(bar + 8 * B_ZX, 1); mbar_init(bar + 8 * B_ZL, 4); mbar_init(bar + 8 * B_RDY, 8);
            mbar_init(bar + 8 * B_AOK, 1); mbar_init(bar + 8 * B_PREP, 1);
            mbar_expect(bar + 8 * B_HX, 16384);
            mbar_expect(bar + 8 * B_ZX, 3328);
            fence_async();
            asm volatile("fence.mbarrier_init.release.cluster;" ::: "memory");
        }
    }
    __syncthreads();
    asm volatile("barrier.cluster.arrive.relaxed.aligned;" ::: "memory");

    if (warp >= 8) {
        asm volatile("setmaxnreg.dec.sync.aligned.u32 40;");
        if (warp == 8) {
            if (lane < 4)
                asm volatile("cp.async.bulk.prefetch.L2.global [%0], 512;" ::"l"(w1g + (3 + lane) * 65536 + blockIdx.x * 512) : "memory");
            __syncwarp();
            int j = 0; uint32_t ph = 0;
#pragma unroll 1
            for (int s = 3; s < 26; s++) {
                const uint32_t off = OFF_P0 + ((j == 2) ? 0 : (j + 1) * 32768);
#pragma unroll
                for (int g = 0; g < 2; g++) {
                    mbar_wait(bar + 8 * (B_W1E + g * 3) + 8 * j, ph);
                    asm volatile("{.reg .pred P; elect.sync _|P,0xffffffff; @P mbarrier.arrive.expect_tx.shared::cta.b64 _, [%2], 16384;"
                                 " @P cp.async.bulk.tensor.3d.shared::cluster.global.mbarrier::complete_tx::bytes [%0],[%1,{%3,%4,%5}],[%2];}"
                                 ::"r"(sb + off + g * 16384), "l"(&tmW1), "r"(bar + 8 * (B_W1F + g * 3) + 8 * j), "r"(0), "r"((int)(s * 128 + c * 64)), "r"(2 * g) : "memory");
                }
                if (s + 4 < 26)
                    asm volatile("{.reg .pred P; elect.sync _|P,0xffffffff; @P cp.async.bulk.prefetch.L2.global [%0], 512;}"
                                 ::"l"(w1g + (uint32_t)((s + 4) * 65536 + blockIdx.x * 512)) : "memory");
                if (++j == 3) { j = 0; ph ^= 1; }
            }
            mbar_wait(bar + 8 * B_PREP, 0);
            asm volatile("fence.proxy.async.global;" ::: "memory");
#pragma unroll 1
            for (int u = 0; u < 64; u++) {
                const int wave = u >> 5, k = (u >> 1) & 15, g = u & 1, slot = u & 7;
                if (k < 4) {
                    if (slot == 0) mbar_wait(bar + 8 * (B_GD + 1) + 32 * wave, 0);
                    if (slot == 4) mbar_wait(wave == 0 ? bar + 8 * B_SD : bar + 8 * (B_GD + 6), 0);
                } else {
                    mbar_wait(bar + 8 * B_WCE + 8 * slot, ((k >> 2) - 1) & 1);
                }
                const uint32_t dst = sb + (wave == 0 ? OFF_B : OFF_L + 8 * S_TILE) + slot * WC_STAGE;
                const uint32_t so = (uint32_t)(((c ^ wave) * 32 + 16 * g + k) * WC_STAGE);
                asm volatile("{.reg .pred P; elect.sync _|P,0xffffffff; @P mbarrier.arrive.expect_tx.shared::cta.b64 _, [%2], 7168;"
                             " @P cp.async.bulk.shared::cluster.global.mbarrier::complete_tx::bytes [%0],[%1],7168,[%2];}"
                             ::"r"(dst), "l"((const char*)g_wc + so), "r"(bar + 8 * B_WCF + 8 * slot) : "memory");
            }
        } else if (warp < 11) {
            const uint32_t ib = sb + OFF_IDX + (lane >> 3) * 32;
            uint32_t o8[8];
            if (warp == 9) {
                const char* tb = table + c * 128 + (lane & 7) * 16;
#pragma unroll 1
                for (int n = 0; n < 26; n++) {
                    lds128(o8, ib + n * 128); lds128(o8 + 4, ib + n * 128 + 16);
                    asm volatile("cp.async.wait_group 3;" ::: "memory");
                    if (n == 0 && lane == 0) STAMP(0);
                    gather_tile<true>(sb + OFF_L + n * S_TILE, o8, tb, lane);
                    cpasync_arrive(bar + 8 * B_AF + 8 * n);
                    asm volatile("cp.async.commit_group;" ::: "memory");
                }
                if (lane == 0) STAMP(1);
            } else {
                const char* tb = table + c * 128 + (lane & 7) * 16;
                const int* ip = idx + (peer0 + lane) * 26;
                int j = 0; uint32_t ph = 1;
#pragma unroll 1
                for (int n = 0; n < 26; n++) {
                    const uint32_t cur = (uint32_t)pidx << 8;
                    if (n < 25) pidx = __ldg(ip + n + 1);
#pragma unroll
                    for (int i = 0; i < 8; i++) o8[i] = __shfl_sync(0xffffffffu, cur, (lane >> 3) + 4 * i);
                    if (n >= 3) mbar_wait(bar + 8 * B_AE + 8 * j, ph);
                    gather_tile<false>(sb + OFF_PEER + j * 4096, o8, tb, lane);
                    cpasync_arrive(bar + 8 * B_AF + 8 * n);
                    if (++j == 3) { j = 0; ph ^= 1; }
                }
            }
            const char* tb = table + (c ^ 1) * 128 + (lane & 7) * 16;
            const int par = warp - 9;
#define RJOB(WAITB, F0, CNT, DST, FULLB)                                                   \
            {                                                                              \
                mbar_wait(bar + 8 * (WAITB), 0);                                           \
                _Pragma("unroll 1")                                                        \
                for (int i = par; i < (CNT); i += 2) {                                     \
                    lds128(o8, ib + ((F0) + i) * 128); lds128(o8 + 4, ib + ((F0) + i) * 128 + 16); \
                    gather_tile<false>(sb + (DST) + i * S_TILE, o8, tb, lane);             \
                }                                                                          \
                if ((FULLB) >= 0) cpasync_arrive(bar + (uint32_t)(8 * ((FULLB) < 0 ? 0 : (FULLB))));                       \
            }
            RJOB(B_FR + 0, 0, 7, OFF_A, -1)
            RJOB(B_FR + 1, 7, 1, OFF_A + 7 * S_TILE, B_RF + 0)
            RJOB(B_FR + 1, 8, 7, OFF_B, -1)
            RJOB(B_FR + 2, 15, 1, OFF_B + 7 * S_TILE, B_RF + 1)
            RJOB(B_FR + 2, 24, 2, OFF_X, B_RF + 3)
            RJOB(B_GD + 0, 16, 8, OFF_A, B_RF + 2)
            RJOB(B_GD + 2, 0, 8, OFF_A, B_RF + 4)
            RJOB(B_TD + 0, 8, 6, OFF_B, -1)
            RJOB(B_TD + 1, 14, 2, OFF_B + 6 * S_TILE, B_RF + 5)
            RJOB(B_GD + 4, 16, 8, OFF_L, B_RF + 6)
#undef RJOB
            asm volatile("cp.async.wait_all;" ::: "memory");
        } else {
            {
                const int b = blockIdx.x;
                if (b < 112) {
                    const int kc = b >> 4, ng = (b >> 2) & 3, eo = (b & 3) * 4 + (lane >> 3), nr = lane & 7;
                    const int n = ng * 8 + nr;
                    const int j = (n < 24) ? n : ((n == 24) ? 24 : (n == 26) ? 25 : -1);
#pragma unroll 1
                    for (int pq = 0; pq < 2; pq++) {
                        uint4 r[4];
#pragma unroll
                        for (int ii = 0; ii < 4; ii++) {
                            const int i = 4 * kc + ii;
                            r[ii] = make_uint4(0, 0, 0, 0);
                            if (j >= 0 && i < 26) r[ii] = __ldg((const uint4*)(wc + (uint32_t)(((pq * 26 + i) * 26 + j) * 256 + eo * 16)));
                        }
                        uint4* dst = g_wc + (uint32_t)(eo * 4 * (WC_STAGE / 16) + pq * (3584 / 16) + kc * 32 + ng * 8 + nr);
                        dst[0 * (WC_STAGE / 16)] = make_uint4(__byte_perm(r[0].x, r[1].x, 0x5410), __byte_perm(r[0].x, r[1].x, 0x7632), __byte_perm(r[2].x, r[3].x, 0x5410), __byte_perm(r[2].x, r[3].x, 0x7632));
                        dst[1 * (WC_STAGE / 16)] = make_uint4(__byte_perm(r[0].y, r[1].y, 0x5410), __byte_perm(r[0].y, r[1].y, 0x7632), __byte_perm(r[2].y, r[3].y, 0x5410), __byte_perm(r[2].y, r[3].y, 0x7632));
                        dst[2 * (WC_STAGE / 16)] = make_uint4(__byte_perm(r[0].z, r[1].z, 0x5410), __byte_perm(r[0].z, r[1].z, 0x7632), __byte_perm(r[2].z, r[3].z, 0x5410), __byte_perm(r[2].z, r[3].z, 0x7632));
                        dst[3 * (WC_STAGE / 16)] = make_uint4(__byte_perm(r[0].w, r[1].w, 0x5410), __byte_perm(r[0].w, r[1].w, 0x7632), __byte_perm(r[2].w, r[3].w, 0x5410), __byte_perm(r[2].w, r[3].w, 0x7632));
                    }
                } else {
#pragma unroll 1
                    for (int q = 0; q < 4; q++) {
                        const int it = (b - 112) * 128 + q * 32 + lane;
                        const int ch = it >> 10, s = (it >> 7) & 7, th = it & 127;
                        const int e = ch * 64 + (th >> 5) * 16 + ((th & 31) >> 2), d = 16 * s + 2 * (th & 3);
                        const unsigned short* p = wbi + d * 128 + e;
                        uint4 v;
                        v.x = __ldg(p) | ((uint32_t)__ldg(p + 128) << 16);
                        v.y = __ldg(p + 8) | ((uint32_t)__ldg(p + 136) << 16);
                        v.z = __ldg(p + 1024) | ((uint32_t)__ldg(p + 1152) << 16);
                        v.w = __ldg(p + 1032) | ((uint32_t)__ldg(p + 1160) << 16);
                        g_wt[it] = v;
                    }
                }
                __threadfence();
                asm volatile("fence.proxy.async.global;" ::: "memory");
                __syncwarp();
                if (lane == 0) {
                    const unsigned tk = atomicAdd(&g_cnt, 1u);
                    const unsigned target = (tk & ~127u) + 128u;
                    unsigned cur; int it = 0;
                    do {
                        asm volatile("ld.acquire.gpu.global.u32 %0,[%1];" : "=r"(cur) : "l"(&g_cnt) : "memory");
                        if ((int)(cur - target) >= 0) break;
                        __nanosleep(200);
                    } while (++it < 100000);
                    mbar_arrive(bar + 8 * B_PREP);
                    STAMP(3);
                }
                __syncwarp();
            }
            const int g = lane >> 2, t = lane & 3;
            uint32_t b1[2][2][2];
#pragma unroll
            for (int nt = 0; nt < 2; nt++)
#pragma unroll
                for (int ks = 0; ks < 2; ks++)
#pragma unroll
                    for (int h = 0; h < 2; h++) {
                        const int f = 16 * ks + 8 * h + 2 * t, r = 8 * nt + g;
                        b1[nt][ks][h] = (f < 26 && r < 13) ? (__ldg(se1 + f * 13 + r) | ((uint32_t)__ldg(se1 + (f + 1) * 13 + r) << 16)) : 0u;
                    }
            if (lane < 6) asm volatile("prefetch.global.L2 [%0];" ::"l"(se2 + lane * 64));
            mbar_wait(bar + 8 * B_ZL, 0);
            mbar_wait_cluster(bar + 8 * B_ZX, 0);
            mbar_wait(bar + 8 * (B_FR + 2), 0);
            const float* zl = (const float*)(sm + OFF_ZL);
            const float* zp = (const float*)(sm + OFF_ZP);
            uint32_t a2[2][4];
#pragma unroll
            for (int mt = 0; mt < 2; mt++) {
                float c1[2][4] = {{0.f, 0.f, 0.f, 0.f}, {0.f, 0.f, 0.f, 0.f}};
#pragma unroll
                for (int ks = 0; ks < 2; ks++) {
                    uint32_t a[4];
#pragma unroll
                    for (int q = 0; q < 4; q++) {
                        const int f = 16 * ks + 8 * (q >> 1) + 2 * t, b = 16 * mt + 8 * (q & 1) + g;
                        const int fc = (f < 26) ? f : 0;
                        const float z0 = (zl[fc * 32 + b] + zp[fc * 32 + b]) * (1.f / 128.f);
                        const float z1 = (zl[fc * 32 + 32 + b] + zp[fc * 32 + 32 + b]) * (1.f / 128.f);
                        a[q] = pack_bf16(z0, z1);
                    }
                    mma16816(c1[0], a, b1[0][ks][0], b1[0][ks][1]);
                    mma16816(c1[1], a, b1[1][ks][0], b1[1][ks][1]);
                    asm volatile("" ::: "memory");
                }
#pragma unroll
                for (int q = 0; q < 4; q++) {
                    float y[2];
#pragma unroll
                    for (int u = 0; u < 2; u++) {
                        const float x = bfr(c1[q >> 1][2 * (q & 1) + u]);
                        const float uu = 1.5957691216057308f * (x + 0.044715f * x * x * x);
                        y[u] = __fdividef(x, 1.f + __expf(-uu));
                    }
                    a2[mt][q] = pack_bf16(y[0], y[1]);
                }
                asm volatile("" ::: "memory");
            }
            uint32_t b2[4][2];
#pragma unroll
            for (int nt = 0; nt < 4; nt++)
#pragma unroll
                for (int h = 0; h < 2; h++) {
                    const int r = 8 * h + 2 * t, f = 8 * nt + g;
                    uint32_t lo = 0, hi = 0;
                    if (f < 26 && r < 13) asm volatile("ld.global.nc.u16 %0,[%1];" : "=r"(lo) : "l"(se2 + r * 26 + f));
                    if (f < 26 && r + 1 < 13) asm volatile("ld.global.nc.u16 %0,[%1];" : "=r"(hi) : "l"(se2 + (r + 1) * 26 + f));
                    b2[nt][h] = lo | (hi << 16);
                }
#pragma unroll
            for (int mt = 0; mt < 2; mt++)
#pragma unroll
                for (int nt = 0; nt < 4; nt++) {
                    float c2[4] = {0.f, 0.f, 0.f, 0.f};
                    mma16816(c2, a2[mt], b2[nt][0], b2[nt][1]);
                    float y[4];
#pragma unroll
                    for (int u = 0; u < 4; u++) y[u] = __fdividef(1.f, 1.f + __expf(-bfr(c2[u])));
                    if (nt < 3 || t == 0) {
                        sts32(sb + OFF_AV + (16 * mt + g) * 56 + (4 * nt + t) * 4, pack_bf16(y[0], y[1]));
                        sts32(sb + OFF_AV + (16 * mt + 8 + g) * 56 + (4 * nt + t) * 4, pack_bf16(y[2], y[3]));
                    }
                }
            __syncwarp();
            if (lane == 0) { mbar_arrive(bar + 8 * B_AOK); STAMP(4); }
        }
        __syncwarp();
        asm volatile("barrier.cluster.wait.aligned;" ::: "memory");
    } else {
        asm volatile("setmaxnreg.inc.sync.aligned.u32 232;");
        const int wg = warp >> 2, w = warp & 3, t = lane & 3;
        const bool el = (lane == 0);
        uint32_t remb; asm("mapa.shared::cluster.u32 %0,%1,%2;" : "=r"(remb) : "r"(sb), "r"(c ^ 1));
        float d[64];
#pragma unroll
        for (int i = 0; i < 64; i++) d[i] = 0.f;
        uint32_t a[2][16];
        uint32_t wf[32], w2r[16];
        const int m = lane >> 3, r = lane & 7;
        const bool ispeer = ((m & 1) ^ wg) != 0;
        uint32_t abase = (ispeer ? sb + OFF_PEER : sb + OFF_L) + (w * 8 + r) * 128 + (m >> 1) * 16;
        const uint32_t astep = ispeer ? 4096 : S_TILE;
        const uint32_t aback = ispeer ? (uint32_t)-8192 : S_TILE;
        uint32_t zaddr = (wg ? remb + OFF_ZP : sb + OFF_ZL) + (w * 8 + (lane >> 2)) * 4;
        const uint32_t zbar = remb + OFF_BAR + 8 * B_ZX;
        constexpr uint32_t dhi = (1024 >> 4) | (1u << 30);
        const uint32_t wd0 = uni(((sb & 0x3FFFF) + wg * 16384) >> 4);
        const uint32_t bF = uni(bar + 8 * B_W1F + wg * 24), bE = bF + 8 * (B_W1E - B_W1F);
        asm volatile("barrier.cluster.wait.aligned;" ::: "memory");

#define LOAD_A(BUF, SLOT)                                                                         \
        {                                                                                         \
            const uint32_t x = swz(abase);                                                        \
            _Pragma("unroll") for (int k = 0; k < 4; k++) ldsm4(&a[BUF][4 * k], x ^ (k * 32));     \
            float z0 = 0.f, z1 = 0.f, z2 = 0.f, z3 = 0.f;                                         \
            _Pragma("unroll") for (int k = 0; k < 4; k++) {                                       \
                z0 += bf_lo(a[BUF][4 * k]); z1 += bf_hi(a[BUF][4 * k]);                           \
                z2 += bf_lo(a[BUF][4 * k + 2]); z3 += bf_hi(a[BUF][4 * k + 2]);                   \
            }                                                                                     \
            float z = (z0 + z1) + (z2 + z3);                                                      \
            z += __shfl_xor_sync(0xffffffffu, z, 1);                                              \
            if (el) mbar_arrive(bar + 8 * (B_AE + (SLOT)));                                       \
            z += __shfl_xor_sync(0xffffffffu, z, 2);                                              \
            if (t == 0) {                                                                         \
                if (wg) asm volatile("st.async.shared::cluster.mbarrier::complete_tx::bytes.f32 [%0],%1,[%2];" ::"r"(zaddr), "f"(z), "r"(zbar) : "memory"); \
                else sts32(zaddr, __float_as_uint(z));                                            \
            }                                                                                     \
            zaddr += 128;                                                                         \
        }

        mbar_wait(bar + 8 * B_AF, 0);
        if (tid == 0) STAMP(2);
        LOAD_A(0, 0)
        mbar_wait(bF, 0);
#pragma unroll 1
        for (int s0 = 0; s0 < 26; s0 += 6) {
#define P1_STEP(q)                                                                                   \
            {                                                                                        \
                constexpr int j = (q) % 3, jn = ((q) + 1) % 3;                                       \
                constexpr uint32_t nph = (((q) + 1) / 3) & 1;                                        \
                constexpr uint32_t dlo = (w1_off(j, 0) >> 4) | ((8192 >> 4) << 16);                  \
                wg_fence();                                                                          \
                wg128_tb<dlo, dhi>(d, &a[(q) & 1][0], wd0);                                          \
                wg128_tb<dlo + 128, dhi>(d, &a[(q) & 1][4], wd0);                                    \
                wg128_tb<dlo + 256, dhi>(d, &a[(q) & 1][8], wd0);                                    \
                wg128_tb<dlo + 384, dhi>(d, &a[(q) & 1][12], wd0);                                   \
                wg_commit();                                                                         \
                if ((q) == 1 && s0 == 24) break;                                                     \
                abase += (jn == 0) ? aback : astep;                                                  \
                mbar_wait(bar + 8 * B_AF + 8 * (s0 + (q) + 1), 0);                                   \
                LOAD_A(((q) + 1) & 1, jn)                                                            \
                if ((q) == 2 && s0 == 18) {     \
                    mbar_wait(bar + 8 * B_PREP, 0);                                                  \
                    const uint4* src = g_wt + c * 1024 + (tid & 127);                                \
                    _Pragma("unroll") for (int k = 0; k < 8; k++) {                                  \
                        const uint4 v = __ldcg(src + ((k ^ (4 * c)) << 7));                          \
                        wf[4 * k] = v.x; wf[4 * k + 1] = v.y; wf[4 * k + 2] = v.z; wf[4 * k + 3] = v.w; \
                    }                                                                                \
                    _Pragma("unroll") for (int k = 0; k < 16; k++)                                   \
                        w2r[k] = __ldg((const uint32_t*)(wd2 + wg * 128 + 8 * k + 2 * t));           \
                }                                                                                    \
                const uint32_t ok = mbar_test(bF + 8 * jn, nph);                                     \
                wg_wait<0>();                                                                        \
                if (el) {                                                                            \
                    mbar_arrive(bE + 8 * j);                                                         \
                    if ((q) == 5 && s0 == 18) mbar_arrive(bar + 8 * B_FR);                           \
                    if ((q) == 0 && s0 == 24) { mbar_arrive(bar + 8 * (B_FR + 1)); if (!wg) mbar_arrive(bar + 8 * B_ZL); } \
                }                                                                                    \
                if (!ok) mbar_wait(bF + 8 * jn, nph);                                                \
                if (tid == 0 && ((q) & 1)) STAMP(8 + ((s0 + (q)) >> 1));                             \
            }
            P1_STEP(0) P1_STEP(1) P1_STEP(2) P1_STEP(3) P1_STEP(4) P1_STEP(5)
#undef P1_STEP
        }
        wg_wait<0>();
        fence_regs<64>(d);
        if (el) {
            mbar_arrive(bar + 8 * (B_FR + 2));
            asm volatile("mbarrier.arrive.relaxed.cluster.shared::cluster.b64 _,[%0];" ::"r"(remb + OFF_BAR + 8 * B_RDY) : "memory");
        }
        if (tid == 0) STAMP(30);
        float hown[32]; uint32_t hsend[16];
#pragma unroll
        for (int k = 0; k < 16; k++) {
            hown[2 * k] = wg ? d[4 * k + 2] : d[4 * k];
            hown[2 * k + 1] = wg ? d[4 * k + 3] : d[4 * k + 1];
            hsend[k] = wg ? pack_bf16(d[4 * k], d[4 * k + 1]) : pack_bf16(d[4 * k + 2], d[4 * k + 3]);
        }
        mbar_wait(bar + 8 * B_RDY, 0);
        if (tid == 0) STAMP(31);
#pragma unroll
        for (int k = 0; k < 4; k++)
            asm volatile("st.async.shared::cluster.mbarrier::complete_tx::bytes.v4.b32 [%0],{%1,%2,%3,%4},[%5];"
                         ::"r"(remb + OFF_SCR + tid * 16 + k * 4096), "r"(hsend[4 * k]), "r"(hsend[4 * k + 1]), "r"(hsend[4 * k + 2]), "r"(hsend[4 * k + 3]),
                         "r"(remb + OFF_BAR + 8 * B_HX) : "memory");
        Ctx cx; cx.sb = sb; cx.bar = bar; cx.wg = wg; cx.w = w; cx.lane = lane;
        const uint32_t cb = uni(((sb & 0x3FFFF) >> 4) + wg * 128);
        float accA[32], accB[32];
        mbar_wait(bar + 8 * B_RF, 0);
        if (tid == 0) STAMP(32);
        fence_async();
        issue_chain64<0, 0, 0>(accA, wf, cb);
        issue_chain64<0, 0, 1>(accB, wf, cb);
        mbar_wait_cluster(bar + 8 * B_HX, 0);
        if (tid == 0) STAMP(33);
        float deep = 0.f;
        {
            uint32_t hr[16];
#pragma unroll
            for (int k = 0; k < 4; k++) lds128(hr + 4 * k, sb + OFF_SCR + tid * 16 + k * 4096);
#pragma unroll
            for (int k = 0; k < 16; k++) { hown[2 * k] += bf_lo(hr[k]); hown[2 * k + 1] += bf_hi(hr[k]); }
            __syncwarp();
            if (el) mbar_arrive(bar + 8 * B_SB);
            float e0 = 0.f, e1 = 0.f;
#pragma unroll
            for (int k = 0; k < 16; k++) {
                const float x0 = hown[2 * k], x1 = hown[2 * k + 1];
                const float t0 = tanh_fast(x0 * fmaf(x0 * x0, 0.035677408136300125f, 0.7978845608028654f));
                const float t1 = tanh_fast(x1 * fmaf(x1 * x1, 0.035677408136300125f, 0.7978845608028654f));
                e0 = fmaf(fmaf(x0, t0, x0), bf_lo(w2r[k]), e0);
                e1 = fmaf(fmaf(x1, t1, x1), bf_hi(w2r[k]), e1);
            }
            deep = 0.5f * (e0 + e1);
            deep += __shfl_xor_sync(0xffffffffu, deep, 1);
            deep += __shfl_xor_sync(0xffffffffu, deep, 2);
            if (t == 0) sts32(sb + OFF_RED + 256 + (wg * 32 + w * 8 + (lane >> 2)) * 4, __float_as_uint(deep));
        }
        if (tid == 0) STAMP(34);
        float logit = 0.f;
        wave_body<0>(cx, c, accA, accB, wf, logit);
        mbar_wait(bar + 8 * (B_RF + 4), 0);
        fence_async();
        const uint32_t cb1 = uni(((sb & 0x3FFFF) >> 4) + wg * 128);
        issue_chain64<1, 0, 0>(accA, wf, cb1);
        issue_chain64<1, 0, 1>(accB, wf, cb1);
        wave_body<1>(cx, c, accA, accB, wf, logit);

        logit += __shfl_xor_sync(0xffffffffu, logit, 1);
        logit += __shfl_xor_sync(0xffffffffu, logit, 2);
        float* red = (float*)(sm + OFF_RED);
        if (t == 0) red[wg * 32 + w * 8 + (lane >> 2)] = logit;
        asm volatile("bar.sync 1, 256;" ::: "memory");
        if (tid < 32) out[own0 + tid] = __float2bfloat16_rn(bfr(red[tid] + red[32 + tid]) + bfr(red[64 + tid] + red[96 + tid]));
        if (tid == 0) STAMP(60);
    }
}

extern "C" void kernel_launch(void* const* d_in, const int* in_sizes, int n_in, void* d_out, int out_size) {
    static CUtensorMap tm;
    static const void* tm_ptr = nullptr;
    if (tm_ptr != d_in[6]) {
        void* fn = nullptr;
        cudaDriverEntryPointQueryResult qr;
        cudaGetDriverEntryPoint("cuTensorMapEncodeTiled", &fn, cudaEnableDefault, &qr);
        typedef CUresult (*PFN)(CUtensorMap*, CUtensorMapDataType, cuuint32_t, void*, const cuuint64_t*, const cuuint64_t*,
                                const cuuint32_t*, const cuuint32_t*, CUtensorMapInterleave, CUtensorMapSwizzle,
                                CUtensorMapL2promotion, CUtensorMapFloatOOBfill);
        cuuint64_t gd[3] = {64, 3328, 4};
        cuuint64_t gs[2] = {512, 128};
        cuuint32_t bd[3] = {64, 64, 2};
        cuuint32_t es[3] = {1, 1, 1};
        ((PFN)fn)(&tm, CU_TENSOR_MAP_DATA_TYPE_BFLOAT16, 3, d_in[6], gd, gs, bd, es, CU_TENSOR_MAP_INTERLEAVE_NONE,
                  CU_TENSOR_MAP_SWIZZLE_128B, CU_TENSOR_MAP_L2_PROMOTION_L2_256B, CU_TENSOR_MAP_FLOAT_OOB_FILL_NONE);
        cudaFuncSetAttribute(fib_kernel, cudaFuncAttributeMaxDynamicSharedMemorySize, SMEM_BYTES);
        tm_ptr = d_in[6];
    }
    fib_kernel<<<128, 384, SMEM_BYTES, cudaStreamPerThread>>>(
        tm, (const int*)d_in[0], (const char*)d_in[1], (const unsigned short*)d_in[2], (const unsigned short*)d_in[3],
        (const unsigned short*)d_in[4], (const char*)d_in[5], (const char*)d_in[6], (const __nv_bfloat16*)d_in[7],
        (__nv_bfloat16*)d_out);
}
```

```cpp
#include <cuda_runtime.h>
#include <cuda_bf16.h>
#include <cuda.h>
#include <stdint.h>

#define STAMP(k) do { } while (0)

#define BOUNDED 0
#define DOTMODE 0
#define RAMP 4
#define DHI 12
#define AL0 5100u
#define GV 1
#define WFPOS 13
#define PFENCE 0
#define PFV 1
#define PSPREAD 2
#define TWAIT 0
constexpr uint32_t S_TILE   = 4224;
constexpr uint32_t OFF_L    = 0;
constexpr uint32_t OFF_BAR  = 26 * S_TILE;
constexpr uint32_t OFF_P0   = 110592;
constexpr uint32_t OFF_PEER = OFF_P0 + 6 * 16384;
constexpr uint32_t OFF_IDX  = OFF_PEER + 3 * 4096;
constexpr uint32_t OFF_PIDX = OFF_IDX + 3328;
constexpr uint32_t OFF_SE   = OFF_PIDX + 3328;
constexpr uint32_t OFF_ZERO = OFF_SE + 2048;
constexpr uint32_t OFF_SEL  = OFF_ZERO + 1024;
constexpr uint32_t OFF_RED  = OFF_SEL + 512;
constexpr uint32_t SMEM_BYTES = OFF_RED + 512;
constexpr uint32_t OFF_A   = OFF_P0;
constexpr uint32_t OFF_B   = OFF_A + 8 * S_TILE;
constexpr uint32_t OFF_SCR = OFF_B + 8 * S_TILE;
constexpr uint32_t OFF_X   = OFF_SCR + 32768;
constexpr uint32_t WC_LBO = 432, WC_TILE = 7 * WC_LBO, WC_STAGE = 2 * WC_TILE;
constexpr uint32_t REL_JIT = 4 * WC_STAGE;
__host__ __device__ constexpr uint32_t wc_slot(int h) { return (h >> 1) * 8 * S_TILE + (h & 1) * 2 * WC_STAGE; }
static_assert(OFF_X + 2 * S_TILE <= OFF_IDX, "X overlap");
static_assert(REL_JIT + 8192 <= 8 * S_TILE && 4 * WC_STAGE + 512 <= 32768, "ring overlap");
static_assert(SMEM_BYTES <= 232448, "smem");
static_assert(2 * S_TILE <= 2 * WC_STAGE && 5 * S_TILE <= 4 * WC_STAGE, "ring release order");

enum {
    B_AF = 0,
    B_GD = 32, B_AE = 40, B_TD = 43, B_SB = 46, B_FR2 = 47, B_WCE = 48,
    B_RDY = 33, B_PREP = 35,
    B_W1F = 56, B_SEF = 62, B_HX = 63, B_WCF = 64,
    B_W1E = 72,
    B_RF = 80,
    B_FR0 = 88, B_FR1 = 89
};

__device__ uint4 g_wc[64 * WC_STAGE / 16 + 64];
__device__ uint4 g_wt[2 * 8 * 128];
__device__ uint4 g_se[128];
__device__ unsigned g_cnt;

__device__ __forceinline__ uint32_t smem_u32(const void* p) { return (uint32_t)__cvta_generic_to_shared(p); }
__device__ __forceinline__ void mbar_init(uint32_t a, uint32_t c) { asm volatile("mbarrier.init.shared::cta.b64 [%0], %1;" ::"r"(a), "r"(c)); }
__device__ __forceinline__ void mbar_expect(uint32_t a, uint32_t b) { asm volatile("mbarrier.arrive.expect_tx.shared::cta.b64 _, [%0], %1;" ::"r"(a), "r"(b) : "memory"); }
__device__ __forceinline__ void mbar_arrive(uint32_t a) { asm volatile("mbarrier.arrive.shared::cta.b64 _, [%0];" ::"r"(a) : "memory"); }
__device__ __forceinline__ uint32_t mbar_test(uint32_t a, uint32_t p) {
    uint32_t done;
    asm volatile("{.reg .pred P; mbarrier.test_wait.parity.shared::cta.b64 P,[%1],%2; selp.u32 %0,1,0,P;}" : "=r"(done) : "r"(a), "r"(p) : "memory");
    return done;
}
__device__ __forceinline__ void mbar_wait(uint32_t a, uint32_t p) {
    if (!BOUNDED)
        asm volatile("{.reg .pred P;\n\tWL: mbarrier.try_wait.parity.shared::cta.b64 P,[%0],%1;\n\t@!P bra WL;\n\t}" ::"r"(a), "r"(p) : "memory");
    else
    asm volatile("{.reg .pred P, Q; .reg .u32 it;\n\t"
                 "mov.u32 it, 0;\n\t"
                 "WL: mbarrier.try_wait.parity.shared::cta.b64 P,[%0],%1;\n\t"
                 "add.u32 it, it, 1;\n\t"
                 "setp.lt.and.u32 Q, it, 100000, !P;\n\t"
                 "@Q bra WL;\n\t"
                 "}" ::"r"(a), "r"(p) : "memory");
}
__device__ __forceinline__ void mbar_wait_pre(uint32_t a, uint32_t p, uint32_t ok) {
    if (!BOUNDED)
        asm volatile("{.reg .pred P;\n\tsetp.ne.u32 P, %2, 0;\n\tWL: @!P mbarrier.try_wait.parity.shared::cta.b64 P,[%0],%1;\n\t@!P bra WL;\n\t}" ::"r"(a), "r"(p), "r"(ok) : "memory");
    else
    asm volatile("{.reg .pred P, Q; .reg .u32 it;\n\t"
                 "setp.ne.u32 P, %2, 0;\n\t"
                 "mov.u32 it, 0;\n\t"
                 "WL: @!P mbarrier.try_wait.parity.shared::cta.b64 P,[%0],%1;\n\t"
                 "add.u32 it, it, 1;\n\t"
                 "setp.lt.and.u32 Q, it, 100000, !P;\n\t"
                 "@Q bra WL;\n\t"
                 "}" ::"r"(a), "r"(p), "r"(ok) : "memory");
}
__device__ __forceinline__ void mbar_wait_cluster(uint32_t a, uint32_t p) {
    asm volatile("{.reg .pred P, Q; .reg .u32 it;\n\t"
                 "mov.u32 it, 0;\n\t"
                 "WL: mbarrier.try_wait.parity.acquire.cluster.shared::cta.b64 P,[%0],%1;\n\t"
                 "add.u32 it, it, 1;\n\t"
                 "setp.lt.and.u32 Q, it, 100000, !P;\n\t"
                 "@Q bra WL;\n\t"
                 "}" ::"r"(a), "r"(p) : "memory");
}
__device__ __forceinline__ void cpasync16(uint32_t dst, const void* src) { asm volatile("cp.async.cg.shared.global [%0],[%1],16;" ::"r"(dst), "l"(src) : "memory"); }
__device__ __forceinline__ void cpasync16_pf(uint32_t dst, const void* src) { asm volatile("cp.async.cg.shared.global.L2::256B [%0],[%1],16;" ::"r"(dst), "l"(src) : "memory"); }
__device__ __forceinline__ void cpasync_arrive(uint32_t bar) { asm volatile("cp.async.mbarrier.arrive.noinc.shared::cta.b64 [%0];" ::"r"(bar) : "memory"); }
__device__ __forceinline__ uint32_t swz(uint32_t a) { return a ^ ((a >> 3) & 0x70); }
__device__ __forceinline__ void ldsm4(uint32_t* r, uint32_t a) {
    asm volatile("ldmatrix.sync.aligned.m8n8.x4.shared.b16 {%0,%1,%2,%3},[%4];" : "=r"(r[0]), "=r"(r[1]), "=r"(r[2]), "=r"(r[3]) : "r"(a) : "memory");
}
__device__ __forceinline__ void ldsm2t(uint32_t& r0, uint32_t& r1, uint32_t a) {
    asm volatile("ldmatrix.sync.aligned.m8n8.x2.trans.shared.b16 {%0,%1},[%2];" : "=r"(r0), "=r"(r1) : "r"(a) : "memory");
}
__device__ __forceinline__ void ldsm4t(uint32_t* r, uint32_t a) {
    asm volatile("ldmatrix.sync.aligned.m8n8.x4.trans.shared.b16 {%0,%1,%2,%3},[%4];" : "=r"(r[0]), "=r"(r[1]), "=r"(r[2]), "=r"(r[3]) : "r"(a) : "memory");
}
__device__ __forceinline__ void stsm4(uint32_t a, uint32_t r0, uint32_t r1, uint32_t r2, uint32_t r3) {
    asm volatile("stmatrix.sync.aligned.m8n8.x4.shared.b16 [%0],{%1,%2,%3,%4};" ::"r"(a), "r"(r0), "r"(r1), "r"(r2), "r"(r3) : "memory");
}
__device__ __forceinline__ void lds128(uint32_t* r, uint32_t a) {
    asm volatile("ld.shared.v4.u32 {%0,%1,%2,%3},[%4];" : "=r"(r[0]), "=r"(r[1]), "=r"(r[2]), "=r"(r[3]) : "r"(a) : "memory");
}
__device__ __forceinline__ uint32_t lds32(uint32_t a) { uint32_t r; asm volatile("ld.shared.u32 %0,[%1];" : "=r"(r) : "r"(a) : "memory"); return r; }
__device__ __forceinline__ void sts32(uint32_t a, uint32_t v) { asm volatile("st.shared.u32 [%0],%1;" ::"r"(a), "r"(v) : "memory"); }
__device__ __forceinline__ uint32_t pack_bf16(float lo, float hi) { uint32_t r; asm("cvt.rn.bf16x2.f32 %0,%1,%2;" : "=r"(r) : "f"(hi), "f"(lo)); return r; }
__device__ __forceinline__ uint32_t mul_bf16x2(uint32_t a, uint32_t b) { uint32_t r; asm volatile("mul.rn.bf16x2 %0,%1,%2;" : "=r"(r) : "r"(a), "r"(b)); return r; }
__device__ __forceinline__ uint32_t fma_bf16x2(uint32_t a, uint32_t b, uint32_t c) { uint32_t r; asm("fma.rn.bf16x2 %0,%1,%2,%3;" : "=r"(r) : "r"(a), "r"(b), "r"(c)); return r; }
__device__ __forceinline__ uint32_t add_bf16x2(uint32_t a, uint32_t b) { uint32_t r; asm volatile("add.rn.bf16x2 %0,%1,%2;" : "=r"(r) : "r"(a), "r"(b)); return r; }
__device__ __forceinline__ uint32_t vxor(uint32_t a, uint32_t b) { uint32_t r; asm volatile("xor.b32 %0,%1,%2;" : "=r"(r) : "r"(a), "r"(b)); return r; }
__device__ __forceinline__ uint32_t vprmt(uint32_t a, uint32_t b, uint32_t c) { uint32_t r; asm volatile("prmt.b32 %0,%1,%2,%3;" : "=r"(r) : "r"(a), "r"(b), "r"(c)); return r; }
__device__ __forceinline__ uint32_t vpack(float lo, float hi) { uint32_t r; asm volatile("cvt.rn.bf16x2.f32 %0,%1,%2;" : "=r"(r) : "f"(hi), "f"(lo)); return r; }
__device__ __forceinline__ float bf_lo(uint32_t x) { return __uint_as_float(x << 16); }
__device__ __forceinline__ float bf_hi(uint32_t x) { return __uint_as_float(x & 0xffff0000u); }
__device__ __forceinline__ float bfr(float x) { return __bfloat162float(__float2bfloat16_rn(x)); }
__device__ __forceinline__ float tanh_fast(float u) { float t; asm("tanh.approx.f32 %0,%1;" : "=f"(t) : "f"(u)); return t; }
__device__ __forceinline__ float ex2f(float u) { float t; asm("ex2.approx.ftz.f32 %0,%1;" : "=f"(t) : "f"(u)); return t; }
__device__ __forceinline__ float rcpf(float u) { float t; asm("rcp.approx.ftz.f32 %0,%1;" : "=f"(t) : "f"(u)); return t; }
__device__ __forceinline__ void wg_fence() { asm volatile("wgmma.fence.sync.aligned;" ::: "memory"); }
__device__ __forceinline__ void wg_commit() { asm volatile("wgmma.commit_group.sync.aligned;" ::: "memory"); }
template <int N> __device__ __forceinline__ void wg_wait() { asm volatile("wgmma.wait_group.sync.aligned %0;" ::"n"(N) : "memory"); }
template <int N> __device__ __forceinline__ void fence_regs(float* d) {
#pragma unroll
    for (int i = 0; i < N; i++) asm volatile("" : "+f"(d[i])::"memory");
}
__device__ __forceinline__ uint32_t uni(uint32_t x) { return __shfl_sync(0xffffffffu, x, 0); }
__device__ __forceinline__ void fence_async() { asm volatile("fence.proxy.async.shared::cta;" ::: "memory"); }
__device__ __forceinline__ void fence_acq_async() { if (PFENCE) fence_async(); else asm volatile("fence.proxy.async::generic.acquire.sync_restrict::shared::cluster.cluster;" ::: "memory"); }
__device__ __forceinline__ uint64_t mk64(uint32_t lo, uint32_t hi) { return ((uint64_t)hi << 32) | lo; }

#define D8(b) "+f"(d[b + 0]), "+f"(d[b + 1]), "+f"(d[b + 2]), "+f"(d[b + 3]), "+f"(d[b + 4]), "+f"(d[b + 5]), "+f"(d[b + 6]), "+f"(d[b + 7])
#define O8(b) "=f"(d[b + 0]), "=f"(d[b + 1]), "=f"(d[b + 2]), "=f"(d[b + 3]), "=f"(d[b + 4]), "=f"(d[b + 5]), "=f"(d[b + 6]), "=f"(d[b + 7])
#define L16 "{%0,%1,%2,%3,%4,%5,%6,%7,%8,%9,%10,%11,%12,%13,%14,%15}"
#define L32 "{%0,%1,%2,%3,%4,%5,%6,%7,%8,%9,%10,%11,%12,%13,%14,%15,%16,%17,%18,%19,%20,%21,%22,%23,%24,%25,%26,%27,%28,%29,%30,%31}"
#define L64 "{%0,%1,%2,%3,%4,%5,%6,%7,%8,%9,%10,%11,%12,%13,%14,%15,%16,%17,%18,%19,%20,%21,%22,%23,%24,%25,%26,%27,%28,%29,%30,%31,%32,%33,%34,%35,%36,%37,%38,%39,%40,%41,%42,%43,%44,%45,%46,%47,%48,%49,%50,%51,%52,%53,%54,%55,%56,%57,%58,%59,%60,%61,%62,%63}"

#define DSC_PRE(B, O, H) "{.reg .b32 lo; .reg .b64 dsc; add.u32 lo, " B ", " O "; mov.b64 dsc, {lo, " H "}; "
template <uint32_t OFF, uint32_t HI> __device__ __forceinline__ void wg128_tb(float* d, const uint32_t* a, uint32_t base) {
    asm volatile(DSC_PRE("%68", "%69", "%70") "wgmma.mma_async.sync.aligned.m64n128k16.f32.bf16.bf16 " L64 ", {%64,%65,%66,%67}, dsc, 1,1,1,1;}"
                 : D8(0), D8(8), D8(16), D8(24), D8(32), D8(40), D8(48), D8(56)
                 : "r"(a[0]), "r"(a[1]), "r"(a[2]), "r"(a[3]), "r"(base), "n"(OFF), "n"(HI));
}
template <bool ACC, uint32_t OFF, uint32_t HI> __device__ __forceinline__ void wg64(float* d, const uint32_t* a, uint32_t base) {
    if (ACC)
        asm volatile(DSC_PRE("%36", "%37", "%38") "wgmma.mma_async.sync.aligned.m64n64k16.f32.bf16.bf16 " L32 ", {%32,%33,%34,%35}, dsc, 1,1,1,0;}"
                     : D8(0), D8(8), D8(16), D8(24) : "r"(a[0]), "r"(a[1]), "r"(a[2]), "r"(a[3]), "r"(base), "n"(OFF), "n"(HI));
    else
        asm volatile(DSC_PRE("%36", "%37", "%38") "wgmma.mma_async.sync.aligned.m64n64k16.f32.bf16.bf16 " L32 ", {%32,%33,%34,%35}, dsc, 0,1,1,0;}"
                     : O8(0), O8(8), O8(16), O8(24) : "r"(a[0]), "r"(a[1]), "r"(a[2]), "r"(a[3]), "r"(base), "n"(OFF), "n"(HI));
}
template <bool ACC, uint32_t OFF, uint32_t HI> __device__ __forceinline__ void wg32(float* d, const uint32_t* a, uint32_t base) {
    if (ACC)
        asm volatile(DSC_PRE("%20", "%21", "%22") "wgmma.mma_async.sync.aligned.m64n32k16.f32.bf16.bf16 " L16 ", {%16,%17,%18,%19}, dsc, 1,1,1,0;}"
                     : D8(0), D8(8) : "r"(a[0]), "r"(a[1]), "r"(a[2]), "r"(a[3]), "r"(base), "n"(OFF), "n"(HI));
    else
        asm volatile(DSC_PRE("%20", "%21", "%22") "wgmma.mma_async.sync.aligned.m64n32k16.f32.bf16.bf16 " L16 ", {%16,%17,%18,%19}, dsc, 0,1,1,0;}"
                     : O8(0), O8(8) : "r"(a[0]), "r"(a[1]), "r"(a[2]), "r"(a[3]), "r"(base), "n"(OFF), "n"(HI));
}
template <bool ACC, bool PERS, uint32_t OFF>
__device__ __forceinline__ void wgsp32(float* d, uint32_t a0, uint32_t a1, uint32_t a2, uint32_t a3, uint32_t base, uint32_t meta) {
    if (PERS) {
        const uint64_t dsc = mk64(base + OFF, 128 >> 4);
        if (ACC)
            asm volatile("wgmma.mma_async.sp.sync.aligned.m64n32k32.f32.bf16.bf16 " L16 ", {%16,%17,%18,%19}, %20, %21, 0, 1,1,1,0;"
                         : D8(0), D8(8) : "r"(a0), "r"(a1), "r"(a2), "r"(a3), "l"(dsc), "r"(meta));
        else
            asm volatile("wgmma.mma_async.sp.sync.aligned.m64n32k32.f32.bf16.bf16 " L16 ", {%16,%17,%18,%19}, %20, %21, 0, 0,1,1,0;"
                         : O8(0), O8(8) : "r"(a0), "r"(a1), "r"(a2), "r"(a3), "l"(dsc), "r"(meta));
    } else {
        if (ACC)
            asm volatile(DSC_PRE("%20", "%22", "8") "wgmma.mma_async.sp.sync.aligned.m64n32k32.f32.bf16.bf16 " L16 ", {%16,%17,%18,%19}, dsc, %21, 0, 1,1,1,0;}"
                         : D8(0), D8(8) : "r"(a0), "r"(a1), "r"(a2), "r"(a3), "r"(base), "r"(meta), "n"(OFF));
        else
            asm volatile(DSC_PRE("%20", "%22", "8") "wgmma.mma_async.sp.sync.aligned.m64n32k32.f32.bf16.bf16 " L16 ", {%16,%17,%18,%19}, dsc, %21, 0, 0,1,1,0;}"
                         : O8(0), O8(8) : "r"(a0), "r"(a1), "r"(a2), "r"(a3), "r"(base), "r"(meta), "n"(OFF));
    }
}

__host__ __device__ constexpr uint32_t w1_off(int j, int g) { return OFF_P0 + ((j + 1) % 3) * 32768 + g * 16384; }

template <bool PF>
__device__ __forceinline__ void gather_tile(uint32_t dst_tile, const uint32_t* off8, const char* tb, int lane) {
    const uint32_t x = dst_tile + (lane >> 3) * 128 + (lane & 7) * 16;
    const uint32_t x0 = swz(x), x1 = swz(x + 512);
#pragma unroll
    for (int i = 0; i < 8; i++) {
        const uint32_t dst = ((i & 1) ? x1 : x0) + (i >> 1) * 1024;
        if (PF) cpasync16_pf(dst, tb + off8[i]); else cpasync16(dst, tb + off8[i]);
    }
}

template <bool ACC, uint32_t HI> __device__ __forceinline__ void wg16(float* d, uint32_t a0, uint32_t a1, uint32_t a2, uint32_t a3, uint32_t lo) {
    if (ACC)
        asm volatile("{.reg .b64 dsc; mov.b64 dsc, {%12, %13}; wgmma.mma_async.sync.aligned.m64n16k16.f32.bf16.bf16 {%0,%1,%2,%3,%4,%5,%6,%7}, {%8,%9,%10,%11}, dsc, 1,1,1,0;}"
                     : D8(0) : "r"(a0), "r"(a1), "r"(a2), "r"(a3), "r"(lo), "n"(HI));
    else
        asm volatile("{.reg .b64 dsc; mov.b64 dsc, {%12, %13}; wgmma.mma_async.sync.aligned.m64n16k16.f32.bf16.bf16 {%0,%1,%2,%3,%4,%5,%6,%7}, {%8,%9,%10,%11}, dsc, 0,1,1,0;}"
                     : O8(0) : "r"(a0), "r"(a1), "r"(a2), "r"(a3), "r"(lo), "n"(HI));
}
template <bool FIRST, int O, uint32_t OFF>
__device__ __forceinline__ void half64(float* acc, const uint32_t* wf, uint32_t base) {
    constexpr uint32_t hi = (S_TILE >> 4) | (1u << 30);
    constexpr uint32_t lo = ((OFF >> 4) + O * 64) | (1u << 16);
    wg64<!FIRST, lo, hi>(acc, wf, base);
    wg64<true, lo + 2, hi>(acc, wf + 4, base);
    wg64<true, lo + 4, hi>(acc, wf + 8, base);
    wg64<true, lo + 6, hi>(acc, wf + 12, base);
}
template <bool FIRST, uint32_t OFF>
__device__ __forceinline__ void half32(float* acc, const uint32_t* wf, uint32_t base) {
    constexpr uint32_t hi = (1024 >> 4) | (1u << 30);
    constexpr uint32_t lo = (OFF >> 4) | (1u << 16);
    wg32<!FIRST, lo, hi>(acc, wf, base);
    wg32<true, lo + 2, hi>(acc, wf + 4, base);
    wg32<true, lo + 4, hi>(acc, wf + 8, base);
    wg32<true, lo + 6, hi>(acc, wf + 12, base);
}
template <int C0> __device__ __forceinline__ void store_half64(const float* acc, uint32_t stb) {
#pragma unroll
    for (int c = C0; c < C0 + 4; c += 2)
        stsm4(stb ^ (c << 4), pack_bf16(acc[4 * c], acc[4 * c + 1]), pack_bf16(acc[4 * c + 2], acc[4 * c + 3]),
              pack_bf16(acc[4 * c + 4], acc[4 * c + 5]), pack_bf16(acc[4 * c + 6], acc[4 * c + 7]));
}
__device__ __forceinline__ void ldg128(uint32_t* r, const char* p) {
    asm volatile("ld.global.v4.u32 {%0,%1,%2,%3},[%4];" : "=r"(r[0]), "=r"(r[1]), "=r"(r[2]), "=r"(r[3]) : "l"(p) : "memory");
}
__device__ __forceinline__ void mbar_arrive2(uint32_t a) { asm volatile("mbarrier.arrive.shared::cta.b64 _, [%0], 2;" ::"r"(a) : "memory"); }
__device__ __forceinline__ void arrive_if(uint32_t a, bool on) {
    asm volatile("{.reg .pred P; setp.ne.u32 P, %1, 0; @P mbarrier.arrive.shared::cta.b64 _, [%0];}" ::"r"(a), "r"((uint32_t)on) : "memory");
}
__device__ __forceinline__ void arrive_cluster(uint32_t a) { asm volatile("mbarrier.arrive.relaxed.cluster.shared::cluster.b64 _,[%0];" ::"r"(a) : "memory"); }
__device__ __forceinline__ uint32_t mapa(uint32_t a, uint32_t r) { uint32_t x; asm("mapa.shared::cluster.u32 %0,%1,%2;" : "=r"(x) : "r"(a), "r"(r)); return x; }
__device__ __forceinline__ int tid_again() { int t; asm volatile("mov.u32 %0, %%tid.x;" : "=r"(t)); return t; }

__global__ void __cluster_dims__(2, 1, 1) __launch_bounds__(384, 1)
fib_kernel(const int* __restrict__ idx, const char* __restrict__ table, const char* __restrict__ wc, const char* __restrict__ w1g,
           const unsigned short* __restrict__ wbi, __nv_bfloat16* __restrict__ out,
           const __grid_constant__ CUtensorMap tmW1,
           const unsigned short* __restrict__ se1, const unsigned short* __restrict__ se2, const __nv_bfloat16* __restrict__ wd2) {
    extern __shared__ __align__(1024) char sm[];
    const uint32_t t_al = clock();
    const uint32_t sb = smem_u32(sm);
    const uint32_t bar = sb + OFF_BAR;
    const int tid = threadIdx.x, lane = tid & 31;
    const uint32_t c = blockIdx.x & 1;
    const int own0 = blockIdx.x * 32, peer0 = own0 ^ 32;

    if (tid < 192) {
        const int n = tid >> 6;
        const bool own = (tid & 32) != 0;
        const int* ip = idx + ((own ? own0 : peer0) + (lane >> 3)) * 26 + n;
        uint32_t o8[8];
#pragma unroll
        for (int i = 0; i < 8; i++) o8[i] = (uint32_t)__ldg(ip + i * 104) << 8;
        if (n) asm volatile("bar.sync 0, 384;" ::: "memory");
        gather_tile<false>(sb + (own ? OFF_L + n * S_TILE : OFF_PEER + n * 4096), o8, table + c * 128 + (lane & 7) * 16, lane);
        if (tid == 0) STAMP(0);
        if (!n) asm volatile("bar.sync 0, 384;" ::: "memory");
        cpasync_arrive(bar + 8 * B_AF + 8 * n);
    }
    const int warp = __shfl_sync(0xffffffffu, tid >> 5, 0);
    if (warp >= 6) {
        if (lane == 0) {
            const uint32_t c0 = (0x800108084040ull >> (8 * (warp - 6))) & 255, c1 = (0x280401084040ull >> (8 * (warp - 6))) & 255;
#pragma unroll
            for (int i = 0; i < 8; i++) { mbar_init(bar + 128 * (warp - 6) + 8 * i, c0); mbar_init(bar + 128 * (warp - 6) + 64 + 8 * i, c1); }
            if (warp == 9) {
#pragma unroll
                for (int i = 0; i < 6; i++) mbar_expect(bar + 8 * (B_W1F + i), 16384);
                mbar_expect(bar + 8 * B_HX, 20480);
#pragma unroll
                for (int g = 0; g < 2; g++)
                    asm volatile("cp.async.bulk.tensor.3d.shared::cluster.global.mbarrier::complete_tx::bytes [%0],[%1,{%3,%4,%5}],[%2];"
                                 ::"r"(sb + w1_off(0, g)), "l"(&tmW1), "r"(bar + 8 * (B_W1F + g * 3)), "r"(0), "r"((int)(c * 64)), "r"(2 * g) : "memory");
            }
            asm volatile("fence.mbarrier_init.release.cluster;" ::: "memory");
        }
        if (warp < 8) {
            const uint32_t one = (tid == 192 + 15) ? 0x3F803F80u : 0u;
#pragma unroll
            for (int i = 0; i < 5; i++) {
                const int e = tid - 288 + 64 * i;
                const uint32_t o = (e < 0) ? OFF_SEL + 512 + e * 16 : OFF_L + (e >> 3) * S_TILE + 4096 + (e & 7) * 16;
                const uint32_t x = (i == 1) ? one : 0u;
                if (e < 208) *(uint4*)(sm + o) = make_uint4(x, x, x, x);
            }
            fence_async();
        }
        __syncwarp();
        asm volatile("bar.sync 4, 192;" ::: "memory");
        asm volatile("bar.arrive 0, 384;" ::: "memory");
        if (warp < 8) {
            const uint32_t x = sb + OFF_L + 22 * S_TILE + (tid - 192) * 16;
            const char* src = (const char*)wbi + (((tid - 192) >> 3) * 256 + c * 128 + (tid & 7) * 16);
#pragma unroll
            for (int k = 0; k < 16; k++) cpasync16(swz(x + (k >> 2) * S_TILE) + (k & 3) * 1024, src + k * 2048);
        }
    }
    asm volatile("barrier.cluster.arrive.relaxed.aligned;" ::: "memory");

    if (warp >= 8) {
        asm volatile("setmaxnreg.dec.sync.aligned.u32 40;");
        if (warp == 8) {
            const char* pf = w1g + (3 * 65536 + blockIdx.x * 512);
            uint32_t ph = 1;
            int row = c * 64;
#pragma unroll 1
            for (int s0 = 0; s0 < 27; s0 += 3) {
#pragma unroll
                for (int j = 0; j < 3; j++) {
                    if (j == 2 && s0 == 24) break;
                    if (j || s0) {
#pragma unroll
                        for (int g = 0; g < 2; g++) {
                            mbar_wait(bar + 8 * (B_W1E + 3 * g + j), ph);
                            asm volatile("{.reg .pred P; elect.sync _|P,0xffffffff;"
                                         " @P cp.async.bulk.tensor.3d.shared::cluster.global.mbarrier::complete_tx::bytes [%0],[%1,{%3,%4,%5}],[%2];}"
                                         ::"r"(sb + w1_off(j, g)), "l"(&tmW1), "r"(bar + 8 * (B_W1F + 3 * g + j)), "r"(0), "r"(row), "r"(2 * g) : "memory");
                        }
                    }
                    if (s0 + j < 23)
                        asm volatile("{.reg .pred P; elect.sync _|P,0xffffffff; @P cp.async.bulk.prefetch.L2.global [%0], 512;}" ::"l"(pf) : "memory");
                    pf += 65536; row += 128;
                }
                ph ^= 1;
            }
            mbar_wait(bar + 8 * B_PREP, 0);
            asm volatile("fence.proxy.async.global;" ::: "memory");
            asm volatile("{.reg .pred P; elect.sync _|P,0xffffffff; @P mbarrier.arrive.expect_tx.shared::cta.b64 _, [%2], 2048;"
                         " @P cp.async.bulk.shared::cluster.global.mbarrier::complete_tx::bytes [%0],[%1],2048,[%2];}"
                         ::"r"(sb + OFF_SE), "l"(g_se), "r"(bar + 8 * B_SEF) : "memory");
        } else {
            const uint32_t ib = sb + OFF_IDX + (lane >> 3) * 32;
            uint32_t o8[8];
            if (warp < 11) {
                {
                    const int2* ip = (const int2*)(idx + ((warp == 9 ? own0 : peer0) + lane) * 26);
                    int2 v[13];
#pragma unroll
                    for (int i = 0; i < 13; i++) v[i] = __ldg(ip + i);
                    const uint32_t ia = sb + (warp == 9 ? OFF_IDX : OFF_PIDX) + ((lane & 3) * 8 + (lane >> 2)) * 4;
#pragma unroll
                    for (int i = 0; i < 13; i++) { sts32(ia + i * 256, (uint32_t)v[i].x << 8); sts32(ia + i * 256 + 128, (uint32_t)v[i].y << 8); }
                    __syncwarp();
                }
                const char* tb = table + c * 128 + (lane & 7) * 16;
                if (warp == 9) {
#pragma unroll 1
                    for (int n = 3; n < 26; n++) {
                        lds128(o8, ib + n * 128); lds128(o8 + 4, ib + n * 128 + 16);
                        const uint32_t o = lds32(sb + OFF_IDX + n * 128 + lane * 4);
                        if (n >= RAMP) mbar_wait(bar + 8 * B_AF + 8 * (n - RAMP), 0);
                        gather_tile<false>(sb + OFF_L + n * S_TILE, o8, tb, lane);
#pragma unroll
                        for (int u = 0; u < (PFV & 7); u++) asm volatile("prefetch.global.L2 [%0];" ::"l"(table + (c ^ 1) * 128 + o + u * (128 / (PFV & 7))));
                        cpasync_arrive(bar + 8 * B_AF + 8 * n);
                        if (PFV == 8) asm volatile("cp.async.cg.shared.global.L2::128B [%0],[%1],16;" ::"r"(sb + OFF_RED + lane * 16), "l"(table + (c ^ 1) * 128 + o) : "memory");
                    }
                } else {
                    int j = 0; uint32_t ph = 0;
#pragma unroll 1
                    for (int n = 3; n < 26; n++) {
                        lds128(o8, ib + 3328 + n * 128); lds128(o8 + 4, ib + 3328 + n * 128 + 16);
                        mbar_wait(bar + 8 * B_AE + 8 * j, ph);
                        gather_tile<false>(sb + OFF_PEER + j * 4096, o8, tb, lane);
                        cpasync_arrive(bar + 8 * B_AF + 8 * n);
                        if (++j == 3) { j = 0; ph ^= 1; }
                    }
                }
            } else {
                const int b = blockIdx.x;
                uint32_t wt0, wt1;
                {
                    const int it = b * 16 + (lane >> 1);
                    const int ch = it >> 10, s = (it >> 7) & 7, th = it & 127;
                    const int e = ch * 64 + (th >> 5) * 16 + ((th & 31) >> 2), d = 16 * s + 2 * (th & 3) + 8 * (lane & 1);
                    const unsigned short* p = wbi + d * 128 + e;
                    wt0 = __ldg(p) | ((uint32_t)__ldg(p + 128) << 16);
                    wt1 = __ldg(p + 8) | ((uint32_t)__ldg(p + 136) << 16);
                }
                if (b < 112) {
                    const int kc = b >> 4, ng = (b >> 2) & 3, eo = (b & 3) * 4 + (lane >> 3), nr = lane & 7;
                    const int n = ng * 8 + nr;
                    const int j = (n < 24) ? n : ((n == 24) ? 24 : (n == 26) ? 25 : -1);
#pragma unroll
                    for (int ii = 0; ii < 4; ii++)
                        if (j >= 0 && 4 * kc + ii < 26) asm volatile("prefetch.global.L2 [%0];" ::"l"(wc + (uint32_t)(((26 + 4 * kc + ii) * 26 + j) * 256 + eo * 16)));
#pragma unroll 1
                    for (int pq = 0; pq < 2 && n <= 26; pq++) {
                        uint4 r[4];
#pragma unroll
                        for (int ii = 0; ii < 4; ii++) {
                            const int i = 4 * kc + ii;
                            r[ii] = make_uint4(0, 0, 0, 0);
                            if (j >= 0 && i < 26) r[ii] = __ldg((const uint4*)(wc + (uint32_t)(((pq * 26 + i) * 26 + j) * 256 + eo * 16)));
                        }
                        uint4* dst = g_wc + (uint32_t)(((eo >> 3) * 32 + (eo & 3) * 8 + ((eo >> 2) & 1)) * (WC_STAGE / 16) + pq * (WC_TILE / 16) + kc * (WC_LBO / 16) + ng * 8 + nr);
                        dst[0 * (WC_STAGE / 8)] = make_uint4(__byte_perm(r[0].x, r[1].x, 0x5410), __byte_perm(r[0].x, r[1].x, 0x7632), __byte_perm(r[2].x, r[3].x, 0x5410), __byte_perm(r[2].x, r[3].x, 0x7632));
                        dst[1 * (WC_STAGE / 8)] = make_uint4(__byte_perm(r[0].y, r[1].y, 0x5410), __byte_perm(r[0].y, r[1].y, 0x7632), __byte_perm(r[2].y, r[3].y, 0x5410), __byte_perm(r[2].y, r[3].y, 0x7632));
                        dst[2 * (WC_STAGE / 8)] = make_uint4(__byte_perm(r[0].z, r[1].z, 0x5410), __byte_perm(r[0].z, r[1].z, 0x7632), __byte_perm(r[2].z, r[3].z, 0x5410), __byte_perm(r[2].z, r[3].z, 0x7632));
                        dst[3 * (WC_STAGE / 8)] = make_uint4(__byte_perm(r[0].w, r[1].w, 0x5410), __byte_perm(r[0].w, r[1].w, 0x7632), __byte_perm(r[2].w, r[3].w, 0x5410), __byte_perm(r[2].w, r[3].w, 0x7632));
                    }
                } else {
                    const int q = b - 112, g = lane >> 2, t = lane & 3;
                    uint32_t lo = 0, hi = 0;
                    if (q < 8) {
                        const int f = 2 * (8 * (q >> 2) + 2 * t + ((q >> 1) & 1)), r = 8 * (q & 1) + g;
                        if (f < 26 && r < 13) { lo = __ldg(se1 + f * 13 + r); hi = __ldg(se1 + f * 13 + 13 + r); }
                    } else {
                        const int r = 8 * ((q - 8) >> 2) + 2 * t, f = 8 * (q & 3) + g;
                        if (f < 26 && r < 13) lo = __ldg(se2 + r * 26 + f);
                        if (f < 26 && r < 12) hi = __ldg(se2 + r * 26 + 26 + f);
                    }
                    ((uint32_t*)g_se)[q * 32 + lane] = lo | (hi << 16);
                }
                ((uint2*)g_wt)[b * 32 + lane] = make_uint2(wt0, wt1);
                __threadfence();
                asm volatile("fence.proxy.async.global;" ::: "memory");
                __syncwarp();
                if (lane == 0) {
                    const unsigned tk = atomicAdd(&g_cnt, 1u);
                    const unsigned target = (tk & ~127u) + 128u;
                    unsigned cur; int it = 0;
#pragma unroll 1
                    do {
                        asm volatile("ld.acquire.gpu.global.u32 %0,[%1];" : "=r"(cur) : "l"(&g_cnt) : "memory");
                        if ((int)(cur - target) >= 0) break;
                        __nanosleep(200);
                    } while (++it < 100000);
                    asm volatile("mbarrier.arrive.shared::cta.b64 _, [%0], 8;" ::"r"(bar + 8 * B_PREP) : "memory");
                    STAMP(3);
                }
                __syncwarp();
            }
        }
        asm volatile("fence.proxy.async.global;" ::: "memory");
        {
            const uint32_t ib = sb + OFF_IDX + (lane >> 3) * 32;
            const char* tb = table + (c ^ 1) * 128 + (lane & 7) * 16;
            const int wq = (warp - 9) & 3;
            uint32_t o8[8];
#pragma unroll 1
            for (int wave = 0; wave < 2; wave++) {
#pragma unroll 1
                for (int f = 8 * wave + wq; f < 26 - 2 * wave; f += 4) {
                    lds128(o8, ib + f * 128); lds128(o8 + 4, ib + f * 128 + 16);
                    const uint32_t wb = wave ? (f < 16 ? B_TD + (f - 7) / 3 : B_GD + 4) : (f < 7 ? B_FR0 : f < 15 ? B_FR1 : f < 16 ? B_FR2 : B_GD);
                    const uint32_t dst = (f < 16) ? OFF_A : (f < 24) ? (wave ? OFF_L : OFF_A) - 16 * S_TILE : OFF_X - 24 * S_TILE;
                    mbar_wait(bar + 8 * wb, 0);
                    if (tid == 288) STAMP(64 + wave * 16 + (f >> 1));
                    gather_tile<false>(sb + dst + f * S_TILE, o8, tb, lane);
                    if (f & 4) cpasync_arrive(bar + 8 * B_RF + 32 * wave + 8 * (f >> 3));
                    if (tid == 288) STAMP(65 + wave * 16 + (f >> 1));
                }
                cpasync_arrive(bar + 8 * (B_RF + 3) + 32 * wave);
                if (wq >= 2) {
                    const uint32_t g = warp & 1;
                    const uint32_t dstw = sb + (wave ? OFF_L + 8 * S_TILE : OFF_B) + g * WC_STAGE;
                    const char* src = (const char*)g_wc + (((c ^ wave) * 32 + g) * WC_STAGE);
#pragma unroll 1
                    for (int u = 0; u < 4; u++) {
#pragma unroll
                        for (int h = 0; h < 4; h++) {
                            mbar_wait(bar + 8 * (B_WCE + h) + 32 * g, u & 1);
                            asm volatile("{.reg .pred P; elect.sync _|P,0xffffffff; @P mbarrier.arrive.expect_tx.shared::cta.b64 _, [%2], 6048;"
                                         " @P cp.async.bulk.shared::cluster.global.mbarrier::complete_tx::bytes [%0],[%1],6048,[%2];}"
                                         ::"r"(dstw + wc_slot(h)), "l"(src + h * 2 * WC_STAGE), "r"(bar + 8 * (B_WCF + h) + 32 * g) : "memory");
                        }
                        src += 8 * WC_STAGE;
                    }
                } else if (wave == 0) {
                    mbar_wait(bar + 8 * (B_GD + 2), 0);
#pragma unroll 1
                    for (int f = wq; f < 8; f += 2) {
                        lds128(o8, ib + f * 128); lds128(o8 + 4, ib + f * 128 + 16);
                        gather_tile<false>(sb + OFF_A + f * S_TILE, o8, tb, lane);
                    }
                    cpasync_arrive(bar + 8 * (B_RF + 4));
                    cpasync_arrive(bar + 8 * (B_RF + 4));
                }
            }
            asm volatile("cp.async.wait_all;" ::: "memory");
        }
        __syncwarp();
        asm volatile("barrier.cluster.wait.aligned;" ::: "memory");
    } else {
        asm volatile("setmaxnreg.inc.sync.aligned.u32 232;");
        const int wg = warp >> 2;
        const bool el = (lane == 0);
        const uint32_t sbm = (sb & 0x3FFFF) >> 4;
        const uint32_t cb = sbm + wg * 128;
        const uint32_t c3 = sbm + wg * (S_TILE >> 4);
        uint32_t wf[32], H[3][32], ai[4] = {0u, 0u, 0u, 0u};
        float accA[32], accB[32];

#define WC_RELEASE2(S, ON) arrive_if(bar + 8 * (B_WCE + (S)) + (tid2 & 1) * 8 + (tid2 & 2) * 16, (tid2 & 31) < 4 && (ON));
#define EW_STEP(W, G, FC, PC, FN, PN, HOOK0, HOOK1, HOOK2, HOOK3)                                                  \
        {                                                                                                   \
            wg_fence();                                                                                     \
            if ((G) > 0) half64<true, 1, 0>(accB, wf, cb + ((FC) >> 4)); else half64<false, 1, 0>(accB, wf + 16, cb + ((PC) >> 4));   \
            wg_commit();                                                                                    \
            HOOK0                                                                                           \
            mbar_wait(bar + 8 * B_SB, (G) & 1);                                            \
            wg_wait<1>();                                                                                   \
            fence_regs<32>(accA);                                                                           \
            store_half64<0>(accA, stb);                                                                     \
            if ((G) > 0) { wg_fence(); half64<false, 1, 0>(accB, wf + 16, cb + ((PC) >> 4)); wg_commit(); }              \
            store_half64<4>(accA, stb);                                                                     \
            { mbar_wait(bar + 8 * (B_RF + (G) + 1) + 32 * (W), 0); fence_acq_async(); } \
            HOOK1                                                                                           \
            wg_fence();                                                                                     \
            if ((G) < 2) half64<true, 0, 0>(accA, wf, cb + ((FN) >> 4)); else half32<true, 0>(accA, wf, c3 + ((FN) >> 4));            \
            wg_commit();                                                                                    \
            wg_wait<1>();                                                                                   \
            fence_regs<32>(accB);                                                                           \
            if ((G) == 1) WC_RELEASE2(0, true)                                                   \
            if ((G) == 2) { if (el) mbar_arrive(bar + 8 * (B_GD + 2) + 32 * (W)); WC_RELEASE2(2, (W) != 0) } \
            store_half64<0>(accB, stb + 8192);                                                              \
            if ((G) < 2) half64<false, 0, 0>(accA, wf + 16, cb + ((PN) >> 4)); else half32<false, 0>(accA, wf + 16, c3 + ((PN) >> 4)); \
            wg_commit();                                                                                    \
            store_half64<4>(accB, stb + 8192);                                                              \
            HOOK2                                                                                           \
            if ((G) < 2) {                                                                                  \
                asm volatile("bar.sync 1, 256;" ::: "memory");                                              \
                _Pragma("unroll") for (int k = 0; k < 16; k++)                                              \
                    ldsm2t(H[(G) & 1][2 * k], H[(G) & 1][2 * k + 1], (ldb ^ ((2 * k & 6) << 4)) + k * 256); \
                if (el) mbar_arrive(bar + 8 * B_SB);                                                        \
            }                                                                                               \
            HOOK3                                                                                           \
            if (tid0) STAMP(36 + (W) * 8 + G);                                                              \
        }

        {
            const int w = warp & 3, t = lane & 3, mm = lane >> 3, rr = lane & 7;
            const bool tid0 = (tid == 0);
            const int tid2 = tid;
            float d[64], zacc[8];
#pragma unroll
            for (int i = 0; i < 64; i++) d[i] = 0.f;
#pragma unroll
            for (int i = 0; i < 8; i++) zacc[i] = 0.f;
            uint32_t w2r[16];
#pragma unroll
            for (int k = 0; k < 16; k++) w2r[k] = __ldg((const uint32_t*)(wd2 + wg * 128 + 8 * k + 2 * t));
            {
                constexpr uint32_t WS = OFF_L + 22 * S_TILE;
                if (warp >= 6) asm volatile("cp.async.wait_all;" ::: "memory");
                asm volatile("bar.sync 1, 256;" ::: "memory");
#pragma unroll
                for (int k = 0; k < 8; k++)
                    ldsm4t(wf + 4 * k, swz(sb + WS + (((k >> 1) ^ 2 ^ (2 * c)) * S_TILE) + ((k & 1) * 16 + (mm >> 1) * 8 + rr) * 128 + (2 * w + (mm & 1)) * 16));
            }
            {
                uint32_t a[2][16];
                const bool el0 = (tid & 127) == 0;
                const uint32_t bid = 2 + wg + lds32(sb + OFF_SEL);
                const bool ispeer = (mm & 1) != 0;
                uint32_t abase = (ispeer ? sb + OFF_PEER : sb + OFF_L) + (w * 8 + rr) * 128 + (mm >> 1) * 16;
                const uint32_t astep = ispeer ? 4096 : S_TILE;
                const uint32_t aback = ispeer ? (uint32_t)-8192 : S_TILE;
                constexpr uint32_t dhi = (1024 >> 4) | (1u << 30);
                const uint32_t wd0 = sbm + wg * 1024;
                uint32_t zd = sbm + ((OFF_SEL + 240) >> 4);
                const uint32_t bF = bar + 8 * B_W1F + wg * 24;
                if (el) mbar_arrive(bar + 8 * B_FR0);
                mbar_wait(bar + 8 * B_AF, 0);
                if (tid0) STAMP(2);
                {
                    const uint32_t x = swz(abase);
#pragma unroll
                    for (int k = 0; k < 4; k++) ldsm4(&a[0][4 * k], x ^ (k * 32));
                    if (el) mbar_arrive(bar + 8 * B_AE);
                }
                mbar_wait(bF, 0);
                if (wg) asm volatile("bar.sync 3, 256;" ::: "memory");
                else while ((uint32_t)clock() - t_al < AL0) {}
#pragma unroll 1
                for (int s0 = 0; s0 < 26; s0 += 6) {
#define P1_REL(q)                                                                                    \
                    {                                                                                \
                        if (el) mbar_arrive(bF + 8 * (B_W1E - B_W1F + (q) % 3));                     \
                        if (el0) mbar_expect(bF + 8 * ((q) % 3), 16384);                             \
                        if (((q) == 5 || (q) == 0) && el) mbar_arrive(bar + 8 * (B_FR0 + ((q) == 0))); \
                    }
#define P1_STEP(q)                                                                                   \
                    {                                                                                \
                        constexpr int j = (q) % 3, jn = ((q) + 1) % 3;                               \
                        constexpr uint32_t nph = (((q) + 1) / 3) & 1;                                \
                        constexpr uint32_t dlo = (w1_off(j, 0) >> 4) | ((8192 >> 4) << 16);          \
                        const uint32_t* aa = a[(q) & 1];                                             \
                        if (wg == ((q) & 1)) {                                                       \
                            wg_fence();                                                              \
                            _Pragma("unroll") for (int k = 0; k < 4; k++)                            \
                                wg16<true, (128 >> 4)>(zacc, aa[4 * k], aa[4 * k + 1], aa[4 * k + 2], aa[4 * k + 3], zd); \
                            zd -= 1;                                                                 \
                        }                                                                            \
                        wg_fence();                                                                  \
                        wg128_tb<dlo, dhi>(d, aa, wd0);                                              \
                        wg128_tb<dlo + 128, dhi>(d, aa + 4, wd0);                                    \
                        wg128_tb<dlo + 256, dhi>(d, aa + 8, wd0);                                    \
                        wg128_tb<dlo + 384, dhi>(d, aa + 12, wd0);                                   \
                        wg_commit();                                                                 \
                        asm volatile("bar.arrive %0, 256;" ::"r"(bid ^ 1) : "memory");               \
                        if ((q) == 1 && s0 == 24) break;                                             \
                        abase += (jn == 0) ? aback : astep;                                          \
                        const uint32_t x = swz(abase);                                               \
                        mbar_wait(bar + 8 * B_AF + 8 * (s0 + (q) + 1), 0);                           \
                        _Pragma("unroll") for (int k = 0; k < 4; k++) ldsm4(&a[((q) + 1) & 1][4 * k], x ^ (k * 32)); \
                        if (el) mbar_arrive(bar + 8 * (B_AE + jn));                                  \
                        const uint32_t ok = mbar_test(bF + 8 * jn, nph);                             \
                        wg_wait<0>();                                                                \
                        P1_REL(q)                                                                    \
                        if (!ok) mbar_wait(bF + 8 * jn, nph);                                        \
                        asm volatile("bar.sync %0, 256;" ::"r"(bid) : "memory");                     \
                        if (tid0 && ((q) & 1)) STAMP(8 + ((s0 + (q)) >> 1));                         \
                    }
                    P1_STEP(0) P1_STEP(1) P1_STEP(2) P1_STEP(3) P1_STEP(4) P1_STEP(5)
#undef P1_STEP
                }
                if (!wg) asm volatile("bar.sync 2, 256;" ::: "memory");
            }
            asm volatile("barrier.cluster.wait.aligned;" ::: "memory");
            const uint32_t remb = mapa(sb, c ^ 1);
            wg_wait<0>();
            fence_regs<64>(d); fence_regs<8>(zacc);
            if (el) { mbar_arrive(bar + 8 * B_FR2); arrive_cluster(remb + OFF_BAR + 8 * B_RDY); }
            if (tid0) STAMP(30);
            uint32_t xm[20];
#pragma unroll
            for (int k = 0; k < 16; k++) xm[k] = pack_bf16(d[4 * k + 2], d[4 * k + 3]);
            xm[16] = __float_as_uint(zacc[2]); xm[17] = __float_as_uint(zacc[3]); xm[18] = __float_as_uint(zacc[6]); xm[19] = __float_as_uint(zacc[7]);
            mbar_wait(bar + 8 * B_RF, 0);
            fence_acq_async();
            const uint32_t stb = sb + OFF_SCR + (2 * wg) * 8192 + (16 * w + 8 * (mm & 1) + rr) * 128 + (((mm >> 1) ^ rr) << 4);
            const uint32_t ldb = sb + OFF_SCR + w * 8192 + (32 * wg + mm) * 128 + ((rr ^ mm) << 4);
            float e0 = 0.f, e1 = 0.f;
            wg_fence();
            half64<true, 0, OFF_A>(accA, wf, cb);
            half64<true, 1, OFF_A>(accB, wf, cb);
            wg_commit();
            mbar_wait(bar + 8 * B_RDY, 0);
            if (tid0) STAMP(31);
#pragma unroll
            for (int k = 0; k < 5; k++)
                asm volatile("st.async.shared::cluster.mbarrier::complete_tx::bytes.v4.b32 [%0],{%1,%2,%3,%4},[%5];"
                             ::"r"(remb + OFF_SCR + tid * 16 + k * 4096), "r"(xm[4 * k]), "r"(xm[4 * k + 1]), "r"(xm[4 * k + 2]), "r"(xm[4 * k + 3]),
                             "r"(remb + OFF_BAR + 8 * B_HX) : "memory");
            wg_wait<0>();
            if (el) mbar_arrive(bar + 8 * B_GD);
            wg_fence();
            half64<false, 0, OFF_L>(accA, wf + 16, cb);
            wg_commit();
            if (tid0) STAMP(32);
#define GELU8(K0)                                                                                           \
            _Pragma("unroll") for (int k = (K0); k < (K0) + 8; k++) {                                       \
                const uint32_t hr = xm[k];                                           \
                const float x0 = d[4 * k] + bf_lo(hr), x1 = d[4 * k + 1] + bf_hi(hr);                       \
                const float t0 = tanh_fast(x0 * fmaf(x0 * x0, 0.035677408136300125f, 0.7978845608028654f)); \
                const float t1 = tanh_fast(x1 * fmaf(x1 * x1, 0.035677408136300125f, 0.7978845608028654f)); \
                e0 = fmaf(fmaf(x0, t0, x0), bf_lo(w2r[k]), e0);                                             \
                e1 = fmaf(fmaf(x1, t1, x1), bf_hi(w2r[k]), e1);                                             \
            }
#define H0_0                                                                                                \
            {                                                                                               \
                mbar_wait_cluster(bar + 8 * B_HX, 0);                                                       \
                if (tid0) STAMP(33);                                                                        \
                _Pragma("unroll") for (int k = 0; k < 5; k++) lds128(xm + 4 * k, sb + OFF_SCR + tid * 16 + k * 4096); \
                if (el) mbar_arrive(bar + 8 * B_SB);            \
            }
#define H0_2                                                                                                \
            {                                                                                               \
                const uint32_t z0 = pack_bf16((zacc[0] + __uint_as_float(xm[16])) * (1.f / 128.f), (zacc[1] + __uint_as_float(xm[17])) * (1.f / 128.f)); \
                const uint32_t z1 = pack_bf16((zacc[4] + __uint_as_float(xm[18])) * (1.f / 128.f), (zacc[5] + __uint_as_float(xm[19])) * (1.f / 128.f)); \
                asm volatile("st.shared.v2.u32 [%0],{%1,%2};" ::"r"(sb + OFF_PIDX + tid * 8), "r"(z0), "r"(z1) : "memory"); \
                GELU8(0)                                                                                    \
                asm volatile("" : "+f"(e0), "+f"(e1));                                                      \
            }
#define H0_3                                                                                                \
            {                                                                                               \
                GELU8(8)                                                                                    \
                float deep = 0.5f * (e0 + e1);                                                              \
                deep += __shfl_xor_sync(0xffffffffu, deep, 1);                                              \
                deep += __shfl_xor_sync(0xffffffffu, deep, 2);                                              \
                if (t == 0) sts32(sb + OFF_RED + 256 + (tid >> 2) * 4, __float_as_uint(deep));              \
                mbar_wait(bar + 8 * B_PREP, 0);                                                             \
                mbar_wait(bar + 8 * B_SEF, 0);                                                              \
            }
            EW_STEP(0, 0, 0, OFF_L, OFF_B, OFF_L + 8 * S_TILE, H0_0, , H0_2, H0_3)
        }
#define H1_1                                                                                                \
            {                                                                                               \
                za[0] = vprmt(y[0], y[2], 0x5410); za[1] = vprmt(y[0], y[2], 0x7632);                       \
                za[2] = vprmt(y[1], y[3], 0x5410); za[3] = vprmt(y[1], y[3], 0x7632);                       \
                wg_fence();                                                                                 \
                wg16<false, (128 >> 4)>(c1, za[0], za[0], za[1], za[1], (sbm + (OFF_SE >> 4)) | ((256 >> 4) << 16)); \
                wg16<true, (128 >> 4)>(c1, za[2], za[2], za[3], za[3], (sbm + ((OFF_SE + 512) >> 4)) | ((256 >> 4) << 16)); \
                wg_commit();                                                                                \
            }
#define H1_2                                                                                                \
            {                                                                                               \
                fence_regs<8>(c1);                                                                          \
                uint32_t a2[4] = {za[0], za[0], za[1], za[1]};                                              \
                if (!wave) _Pragma("unroll") for (int q = 0; q < 2; q++) {                                  \
                    const uint32_t xx = pack_bf16(c1[4 * q], c1[4 * q + 1]);                                \
                    const float x0 = bf_lo(xx), x1 = bf_hi(xx);               \
                    const float y0 = x0 * rcpf(1.f + ex2f(x0 * fmaf(x0 * x0, -0.10294324f, -2.30220819f))); \
                    const float y1 = x1 * rcpf(1.f + ex2f(x1 * fmaf(x1 * x1, -0.10294324f, -2.30220819f))); \
                    a2[2 * q] = a2[2 * q + 1] = vpack(y0, y1);                                              \
                }                                                                                           \
                wg_fence();                                                                                 \
                wg32<false, ((OFF_SE + 1024) >> 4) | ((512 >> 4) << 16), (128 >> 4)>(c2, a2, sbm);          \
                wg_commit();                                                                                \
            }
#define H2_1                                                                                                \
            if (!wave) {                                                                                               \
                fence_regs<16>(c2);                                                                         \
                _Pragma("unroll") for (int nt = 0; nt < 4; nt++) {                                          \
                    const uint32_t xx = pack_bf16(c2[4 * nt], c2[4 * nt + 1]);                              \
                    ai[nt] = vpack(rcpf(1.f + ex2f(bf_lo(xx) * -1.4426950408889634f)), rcpf(1.f + ex2f(bf_hi(xx) * -1.4426950408889634f))); \
                }                                                                                           \
                ai[3] = __shfl_sync(0xffffffffu, ai[3], tid2 & 28);                                         \
            }

        float s0 = 0.f, s1 = 0.f;
#pragma unroll 1
        for (int wave = 0;; wave++) {
            {
                const int tid2 = tid_again();
                const int w = (tid2 >> 5) & 3, mm = (tid2 >> 3) & 3, rr = tid2 & 7, g = (tid2 >> 2) & 7, t = tid2 & 3;
                const bool tid0 = (tid2 == 0);
                const uint32_t PB0 = wave ? OFF_A : OFF_L, PD2 = wave ? OFF_L - OFF_A : 16 * S_TILE, PB3 = wave ? OFF_X : OFF_L + 24 * S_TILE;
                const uint32_t FB1 = wave ? OFF_L + 8 * S_TILE : OFF_B, FB2 = wave ? OFF_L + 16 * S_TILE : OFF_A, FB3 = wave ? OFF_L + 24 * S_TILE : OFF_X;
                {
                    const uint32_t stb = sb + OFF_SCR + (2 * wg) * 8192 + (16 * w + 8 * (mm & 1) + rr) * 128 + (((mm >> 1) ^ rr) << 4);
                    const uint32_t ldb = sb + OFF_SCR + w * 8192 + (32 * wg + mm) * 128 + ((rr ^ mm) << 4);
                    float c1[8], c2[16];
                    uint32_t za[4], y[4];
                    asm volatile("ld.shared.v2.u32 {%0,%1},[%2];" : "=r"(y[0]), "=r"(y[1]) : "r"(sb + OFF_PIDX + (tid2 & 127) * 8) : "memory");
                    asm volatile("ld.shared.v2.u32 {%0,%1},[%2];" : "=r"(y[2]), "=r"(y[3]) : "r"(sb + OFF_PIDX + 1024 + (tid2 & 127) * 8) : "memory");
                    EW_STEP(wave, 1, FB1, PB0 + 8 * S_TILE, FB2, PB0 + PD2, , H1_1, H1_2, )
                    EW_STEP(wave, 2, FB2, PB0 + PD2, FB3, PB3, , H2_1, , )
                }
                const uint32_t zero = lds32(sb + OFF_SEL);
                const uint32_t row = sb + (8 * w + g) * 128;
                const uint32_t pb0 = swz(row + PB0 + (2 * t) * S_TILE) ^ (64 * wg);
                const uint32_t pb1 = swz(row + PB0 + (2 * t + 1) * S_TILE) ^ (64 * wg);
                const uint32_t pb6 = (t < 2) ? swz(row + PB3 + t * S_TILE) ^ (64 * wg) : sb + OFF_ZERO;
                const uint32_t jaddr = (rr < 2) ? sb + FB1 + REL_JIT + w * 2048 + (32 * wg + (mm & 1)) * 32 + rr * 16 : sb + OFF_ZERO;
                uint32_t pr[2][7][4];
#define T_PARTQ(b, q) lds128(pr[(b) & 1][q], (((q) == 6 ? pb6 : ((q) & 1) ? pb1 : pb0) ^ ((b) << 4)) + ((q) == 6 || (q) < 2 ? 0u : (q) < 4 ? 8 * S_TILE : PD2));
                wg_wait<0>();
                fence_regs<16>(accA);
                {
                    const uint32_t jb = sb + FB1 + REL_JIT + (mm >> 1) * 2048 + (16 * w + 8 * (mm & 1) + rr) * 32 + wg * 16;
                    stsm4(jb, pack_bf16(accA[0], accA[1]), pack_bf16(accA[2], accA[3]), pack_bf16(accA[4], accA[5]), pack_bf16(accA[6], accA[7]));
                    stsm4(jb + 4096, pack_bf16(accA[8], accA[9]), pack_bf16(accA[10], accA[11]), pack_bf16(accA[12], accA[13]), pack_bf16(accA[14], accA[15]));
                }
                float aj[7];
#pragma unroll
                for (int q = 0; q < 3; q++) { aj[2 * q] = bf_lo(ai[q] ^ zero); aj[2 * q + 1] = bf_hi(ai[q] ^ zero); }
                aj[6] = (t & 1) ? bf_hi(ai[3]) : bf_lo(ai[3]);
                const uint32_t meta = 0xEEEE4444u ^ zero;
                mbar_wait(bar + 32 * wg + 8 * B_WCF, 0);
                asm volatile("bar.sync 1, 256;" ::: "memory");
                if (tid0) STAMP(36 + wave * 8 + 3);
                constexpr uint32_t ring = (WC_LBO >> 4) << 16;
                const uint32_t rb = sbm + wg * (WC_STAGE >> 4) + (FB1 >> 4);
                const uint32_t bw = bar + 32 * wg;
                float tp[2][16], tq[2][16];
                uint32_t jj[2][2], hh[2][2], v[2][8];
#define T_JIT(k) ldsm2t(jj[(k) & 1][0], jj[(k) & 1][1], jaddr + (k) * 64);
#define T_PREP(k)                                                                                   \
                {                                                                                   \
                    uint32_t* vv = v[(k) & 1];                                                      \
                    vv[0] = mul_bf16x2(H[0][2 * (k)], ai[0]); vv[1] = mul_bf16x2(H[0][2 * (k) + 1], ai[0]); \
                    vv[2] = mul_bf16x2(H[1][2 * (k)], ai[1]); vv[3] = mul_bf16x2(H[1][2 * (k) + 1], ai[1]); \
                    vv[4] = mul_bf16x2(H[2][2 * (k)], ai[2]); vv[5] = mul_bf16x2(H[2][2 * (k) + 1], ai[2]); \
                    hh[(k) & 1][0] = vxor(H[2][2 * (k)], zero); hh[(k) & 1][1] = vxor(H[2][2 * (k) + 1], zero); \
                    vv[6] = mul_bf16x2(jj[(k) & 1][0], ai[3]); vv[7] = mul_bf16x2(jj[(k) & 1][1], ai[3]); \
                }
#define T_ISSUE(k)                                                                                  \
                {                                                                                   \
                    constexpr uint32_t lo = ring + (wc_slot((k) & 3) >> 4);                 \
                    constexpr int n0 = 4 * ((k) & 3);                                               \
                    const uint32_t* vv = v[(k) & 1];                                                \
                    wg_fence();                                                                     \
                    wgsp32<false, (n0 < DHI), lo>(tp[(k) & 1], H[0][2 * (k)], H[0][2 * (k) + 1], H[1][2 * (k)], H[1][2 * (k) + 1], rb, meta); \
                    wgsp32<false, (n0 + 1 < DHI), lo + (WC_TILE >> 4)>(tq[(k) & 1], vv[0], vv[1], vv[2], vv[3], rb, meta); \
                    wgsp32<true, (n0 + 2 < DHI), lo + (4 * WC_LBO >> 4)>(tp[(k) & 1], hh[(k) & 1][0], hh[(k) & 1][1], jj[(k) & 1][0], jj[(k) & 1][1], rb, meta); \
                    wgsp32<true, (n0 + 3 < DHI), lo + ((WC_TILE + 4 * WC_LBO) >> 4)>(tq[(k) & 1], vv[4], vv[5], vv[6], vv[7], rb, meta); \
                    wg_commit();                                                                    \
                }
#define T_FMA(p)                                                                                    \
                {                                                                                   \
                    const float* P = tp[(p) & 1];                                                   \
                    const float* Q = tq[(p) & 1];                                                   \
                    if (DOTMODE == 0) {                                                             \
                        _Pragma("unroll") for (int q = 0; q < 7; q++) {                             \
                            const int di = 4 * (q >> 1) + (q & 1);                                  \
                            const uint32_t x = pr[((p) >> 2) & 1][q][(p) & 3];                                      \
                            s0 = fmaf(bf_lo(x), fmaf(aj[q], Q[di], P[di]), s0);                     \
                            s1 = fmaf(bf_hi(x), fmaf(aj[q], Q[di + 2], P[di + 2]), s1);             \
                        }                                                                           \
                    } else {                                                                        \
                        uint32_t acc2 = 0;                                                          \
                        _Pragma("unroll") for (int q = 0; q < 7; q++) {                             \
                            const int di = 4 * (q >> 1) + (q & 1);                                  \
                            acc2 = fma_bf16x2(pr[((p) >> 2) & 1][q][(p) & 3], pack_bf16(fmaf(aj[q], Q[di], P[di]), fmaf(aj[q], Q[di + 2], P[di + 2])), acc2); \
                        }                                                                           \
                        s0 += bf_lo(acc2); s1 += bf_hi(acc2);                                       \
                    }                                                                               \
                    asm volatile("" : "+f"(s0), "+f"(s1));                                          \
                    if ((p) < 12) {      \
                        constexpr int nb = ((p) >> 2) + 1, ph = (p) & 3;                            \
                        if (nb == 1 && PSPREAD < 2) {                                               \
                            if (ph == 3) { T_PARTQ(nb, 0) T_PARTQ(nb, 1) T_PARTQ(nb, 2) T_PARTQ(nb, 3) T_PARTQ(nb, 4) T_PARTQ(nb, 5) T_PARTQ(nb, 6) } \
                        } else if (nb == 1) {                                                       \
                            if (ph == 2) { T_PARTQ(nb, 0) T_PARTQ(nb, 1) T_PARTQ(nb, 2) }           \
                            if (ph == 3) { T_PARTQ(nb, 3) T_PARTQ(nb, 4) T_PARTQ(nb, 5) T_PARTQ(nb, 6) } \
                        } else {                                                                    \
                            if (ph == 0) { T_PARTQ(nb, 0) }                                         \
                            if (ph == 1) { T_PARTQ(nb, 1) T_PARTQ(nb, 2) }                          \
                            if (ph == 2) { T_PARTQ(nb, 3) T_PARTQ(nb, 4) }                          \
                            if (ph == 3) { T_PARTQ(nb, 5) T_PARTQ(nb, 6) }                          \
                        }                                                                           \
                    }                                                                               \
                }
#define T_DONE(k)                                                                                   \
                {                                                                                   \
                    fence_regs<16>(tp[(k) & 1]); fence_regs<16>(tq[(k) & 1]);                       \
                    if ((k) < 12) { if (el) mbar_arrive2(bw + 8 * (B_WCE + ((k) & 3))); }           \
                    else if (el) mbar_arrive(bar + 8 * (B_TD + (k) - 12));        \
                }
#define T_STEP(k)                                                                                   \
                {                                                                                   \
                    constexpr int kn = ((k) < 15) ? (k) + 1 : 15, kp = ((k) > 0) ? (k) - 1 : 0;     \
                    if (TWAIT == 0) mbar_wait_pre(bw + 8 * (B_WCF + ((k) & 3)), ((k) >> 2) & 1, ok); \
                    if (TWAIT == 1) { if (!ok) mbar_wait(bw + 8 * (B_WCF + ((k) & 3)), ((k) >> 2) & 1); } \
                    if (TWAIT == 2) mbar_wait(bw + 8 * (B_WCF + ((k) & 3)), ((k) >> 2) & 1);       \
                    T_ISSUE(k)                                                                      \
                    if ((k) > 0) { wg_wait<1>(); T_DONE(kp) }                                       \
                    if ((k) < 15) {                                                                 \
                        T_JIT(kn)                                                                   \
                        if (TWAIT < 2) ok = mbar_test(bw + 8 * (B_WCF + (kn & 3)), (kn >> 2) & 1); \
                    }                                                                               \
                    if ((k) > 0) T_FMA(kp)                                                          \
                    if (WFPOS == 0 && (k) >= 10 && (k) <= 13) {   \
                        constexpr int u = ((k) - 10) & 3;                                           \
                        ldg128(wf + 4 * u, wsrc2 + c * 8192 + u * 2048);                            \
                        ldg128(wf + 16 + 4 * u, wsrc2 + (c ^ 1) * 8192 + u * 2048);                 \
                    }                                                                               \
                    if (WFPOS && ((k) == WFPOS || (k) == WFPOS + 1)) {                              \
                        constexpr int u = ((k) - WFPOS) & 1;                                        \
                        _Pragma("unroll") for (int i = 0; i < 4; i++) ldg128(wf + 16 * u + 4 * i, wsrc2 + (c ^ u) * 8192 + i * 2048); \
                    }                                                                               \
                    if ((k) < 15) T_PREP(kn)                                                        \
                }
                uint32_t ok = 0;
                const char* wsrc2 = (const char*)g_wt + ((c ^ 1) * 16384 + (tid2 & 127) * 16);
                {
                    const uint32_t ldb = sb + OFF_SCR + w * 8192 + (32 * wg + mm) * 128 + ((rr ^ mm) << 4);
                    T_JIT(0)
                    ldsm4t(&H[2][0], ldb);
                    T_JIT(1)
                    ok = mbar_test(bw + 8 * (B_WCF + 1), 0);
#pragma unroll
                    for (int k = 1; k < 8; k++) ldsm4t(&H[2][4 * k], (ldb ^ ((k & 1) << 6)) + k * 512);
                    if (el) mbar_arrive(bar + 8 * B_SB);
                    WC_RELEASE2(2, wave == 0)
                    T_PREP(0)
                    T_ISSUE(0)
                    T_PARTQ(0, 0) T_PARTQ(0, 1) T_PARTQ(0, 2) T_PARTQ(0, 3) T_PARTQ(0, 4) T_PARTQ(0, 5) T_PARTQ(0, 6)
                    T_PREP(1)
                }
                T_STEP(1) T_STEP(2) T_STEP(3) T_STEP(4) T_STEP(5) T_STEP(6) T_STEP(7)
                T_STEP(8) T_STEP(9) T_STEP(10) T_STEP(11) T_STEP(12) T_STEP(13) T_STEP(14)
                mbar_wait_pre(bw + 8 * (B_WCF + 3), 1, ok);
                T_ISSUE(15)
                wg_wait<1>();
                T_DONE(14)
                wg_fence();
                half64<true, 0, OFF_L>(accA, wf, cb);
                wg_commit();
                T_FMA(14)
                wg_wait<1>();
                T_DONE(15)
                if (GV == 2) { wg_fence(); half64<true, 1, OFF_L>(accB, wf, cb); wg_commit(); }
                T_FMA(15)
                if (tid0) STAMP(40 + 8 * wave);
            }
            if (wave) break;
            if (GV == 1) { wg_fence(); half64<true, 1, OFF_L>(accB, wf, cb); wg_commit(); }
            {
                const int tid2 = tid_again();
                const int w = (tid2 >> 5) & 3, mm = (tid2 >> 3) & 3, rr = tid2 & 7;
                const bool tid0 = (tid2 == 0);
                const uint32_t stb = sb + OFF_SCR + (2 * wg) * 8192 + (16 * w + 8 * (mm & 1) + rr) * 128 + (((mm >> 1) ^ rr) << 4);
                const uint32_t ldb = sb + OFF_SCR + w * 8192 + (32 * wg + mm) * 128 + ((rr ^ mm) << 4);
                mbar_wait(bar + 8 * (B_RF + 4), 0);
                fence_acq_async();
                wg_fence();
                half64<false, 0, OFF_A>(accA, wf + 16, cb);
                wg_commit();
                wg_wait<1>();
                if (el) mbar_arrive(bar + 8 * (B_GD + 4));
                EW_STEP(1, 0, 0, OFF_A, OFF_L + 8 * S_TILE, OFF_B, , , , )
            }
        }
        float logit = s0 + s1;
        logit += __shfl_xor_sync(0xffffffffu, logit, 1);
        logit += __shfl_xor_sync(0xffffffffu, logit, 2);
        float* red = (float*)(sm + OFF_RED);
        const int tid3 = tid_again();
        if ((tid3 & 3) == 0) red[tid3 >> 2] = logit;
        asm volatile("bar.sync 1, 256;" ::: "memory");
        if (tid3 < 32) out[own0 + tid3] = __float2bfloat16_rn(bfr(red[tid3] + red[32 + tid3]) + bfr(red[64 + tid3] + red[96 + tid3]));
        wg_wait<0>();
        if (tid3 == 0) STAMP(60);
    }
}

extern "C" void kernel_launch(void* const* d_in, const int* in_sizes, int n_in, void* d_out, int out_size) {
    static CUtensorMap tm;
    static const void* tm_ptr = nullptr;
    if (tm_ptr != d_in[6]) {
        void* fn = nullptr;
        cudaDriverEntryPointQueryResult qr;
        cudaGetDriverEntryPoint("cuTensorMapEncodeTiled", &fn, cudaEnableDefault, &qr);
        typedef CUresult (*PFN)(CUtensorMap*, CUtensorMapDataType, cuuint32_t, void*, const cuuint64_t*, const cuuint64_t*,
                                const cuuint32_t*, const cuuint32_t*, CUtensorMapInterleave, CUtensorMapSwizzle,
                                CUtensorMapL2promotion, CUtensorMapFloatOOBfill);
        cuuint64_t gd[3] = {64, 3328, 4};
        cuuint64_t gs[2] = {512, 128};
        cuuint32_t bd[3] = {64, 64, 2};
        cuuint32_t es[3] = {1, 1, 1};
        ((PFN)fn)(&tm, CU_TENSOR_MAP_DATA_TYPE_BFLOAT16, 3, d_in[6], gd, gs, bd, es, CU_TENSOR_MAP_INTERLEAVE_NONE,
                  CU_TENSOR_MAP_SWIZZLE_128B, CU_TENSOR_MAP_L2_PROMOTION_L2_256B, CU_TENSOR_MAP_FLOAT_OOB_FILL_NONE);
        cudaFuncSetAttribute(fib_kernel, cudaFuncAttributeMaxDynamicSharedMemorySize, SMEM_BYTES);
        tm_ptr = d_in[6];
    }
    fib_kernel<<<128, 384, SMEM_BYTES, cudaStreamPerThread>>>(
        (const int*)d_in[0], (const char*)d_in[1], (const char*)d_in[5], (const char*)d_in[6], (const unsigned short*)d_in[4],
        (__nv_bfloat16*)d_out, tm, (const unsigned short*)d_in[2], (const unsigned short*)d_in[3], (const __nv_bfloat16*)d_in[7]);
}
```

```cpp
#include <cuda_runtime.h>
#include <cuda_bf16.h>
#include <cuda.h>
#include <stdint.h>

#define STAMP(k) do { } while (0)

#define BOUNDED 0
#define DOTMODE 0
#define RAMP 4
#define DHI 12
#define AL0 4500u
#define GV 1
#define WFPOS 12
#define PFENCE 0
#define RSL 0
#define BE 0
#define RELPOS 0
#define AEPOS 1
#define GPOS 1
#define SPOS 1
#define W1PRE 1
#define W1PF 1
#define PN 4
#define PT0 0u
#define PP 0u
#define PSPREAD 2
#define TWAIT 0
constexpr uint32_t S_TILE   = 4224;
constexpr uint32_t OFF_L    = 0;
constexpr uint32_t OFF_BAR  = 26 * S_TILE;
constexpr uint32_t OFF_P0   = 110592;
__host__ __device__ constexpr uint32_t peer_off(int j) { return OFF_P0 + j * 4096 + (j ? 98304 : 0); }
constexpr uint32_t OFF_IDX  = OFF_P0 + 6 * 16384 + 3 * 4096;
constexpr uint32_t OFF_PIDX = OFF_IDX + 3328;
constexpr uint32_t OFF_SE   = OFF_PIDX + 3328;
constexpr uint32_t OFF_ZERO = OFF_SE + 2048;
constexpr uint32_t OFF_SEL  = OFF_ZERO + 1024;
constexpr uint32_t OFF_RED  = OFF_SEL + 512;
constexpr uint32_t OFF_W2   = OFF_RED + 512;
constexpr uint32_t SMEM_BYTES = OFF_W2 + 512;
constexpr uint32_t OFF_A   = OFF_P0;
constexpr uint32_t OFF_B   = OFF_A + 8 * S_TILE;
constexpr uint32_t OFF_SCR = OFF_B + 8 * S_TILE;
constexpr uint32_t OFF_X   = OFF_SCR + 32768;
constexpr uint32_t WC_LBO = 432, WC_TILE = 7 * WC_LBO, WC_STAGE = 6144;
constexpr uint32_t REL_JIT = 4 * WC_STAGE;
__host__ __device__ constexpr uint32_t wc_slot(int h) { return (h >> 1) * 8 * S_TILE + (h & 1) * 2 * WC_STAGE; }
static_assert(OFF_X + 2 * S_TILE <= OFF_IDX, "X overlap");
static_assert(REL_JIT + 8192 <= 8 * S_TILE && 4 * WC_STAGE + 512 <= 32768, "ring overlap");
static_assert(SMEM_BYTES <= 232448, "smem");
static_assert(RAMP <= 4, "temporary tiles of the peeled steps are reused by look-ahead loads");
static_assert(2 * S_TILE <= 2 * WC_STAGE && 5 * S_TILE <= 4 * WC_STAGE, "ring release order");

enum {
    B_AF = 0,
    B_GD = 32, B_AE = 40, B_TD = 43, B_SB = 46, B_FR2 = 47, B_WCE = 48,
    B_SEF = 33, B_PREP = 35,
    B_W1F = 56, B_HX = 62, B_WCF = 64,
    B_W1E = 72, B_RDY = 78,
    B_RF = 80,
    B_FR0 = 88, B_FR1 = 89
};

__device__ uint4 g_wc[64 * WC_STAGE / 16 + 64];
__device__ uint4 g_wt[2 * 8 * 128];
__device__ uint4 g_se[128];
__device__ unsigned g_cnt;

__device__ __forceinline__ uint32_t smem_u32(const void* p) { return (uint32_t)__cvta_generic_to_shared(p); }
__device__ __forceinline__ void mbar_init(uint32_t a, uint32_t c) { asm volatile("mbarrier.init.shared::cta.b64 [%0], %1;" ::"r"(a), "r"(c)); }
__device__ __forceinline__ void mbar_expect(uint32_t a, uint32_t b) { asm volatile("mbarrier.arrive.expect_tx.shared::cta.b64 _, [%0], %1;" ::"r"(a), "r"(b) : "memory"); }
__device__ __forceinline__ void mbar_arrive(uint32_t a) { asm volatile("mbarrier.arrive.shared::cta.b64 _, [%0];" ::"r"(a) : "memory"); }
__device__ __forceinline__ uint32_t mbar_test(uint32_t a, uint32_t p) {
    uint32_t done;
    asm volatile("{.reg .pred P; mbarrier.test_wait.parity.shared::cta.b64 P,[%1],%2; selp.u32 %0,1,0,P;}" : "=r"(done) : "r"(a), "r"(p) : "memory");
    return done;
}
__device__ __forceinline__ void mbar_wait(uint32_t a, uint32_t p) {
    if (!BOUNDED)
        asm volatile("{.reg .pred P;\n\tWL: mbarrier.try_wait.parity.shared::cta.b64 P,[%0],%1;\n\t@!P bra WL;\n\t}" ::"r"(a), "r"(p) : "memory");
    else
    asm volatile("{.reg .pred P, Q; .reg .u32 it;\n\t"
                 "mov.u32 it, 0;\n\t"
                 "WL: mbarrier.try_wait.parity.shared::cta.b64 P,[%0],%1;\n\t"
                 "add.u32 it, it, 1;\n\t"
                 "setp.lt.and.u32 Q, it, 100000, !P;\n\t"
                 "@Q bra WL;\n\t"
                 "}" ::"r"(a), "r"(p) : "memory");
}
__device__ __forceinline__ void mbar_wait_pre(uint32_t a, uint32_t p, uint32_t ok) {
    if (!BOUNDED)
        asm volatile("{.reg .pred P;\n\tsetp.ne.u32 P, %2, 0;\n\tWL: @!P mbarrier.try_wait.parity.shared::cta.b64 P,[%0],%1;\n\t@!P bra WL;\n\t}" ::"r"(a), "r"(p), "r"(ok) : "memory");
    else
    asm volatile("{.reg .pred P, Q; .reg .u32 it;\n\t"
                 "setp.ne.u32 P, %2, 0;\n\t"
                 "mov.u32 it, 0;\n\t"
                 "WL: @!P mbarrier.try_wait.parity.shared::cta.b64 P,[%0],%1;\n\t"
                 "add.u32 it, it, 1;\n\t"
                 "setp.lt.and.u32 Q, it, 100000, !P;\n\t"
                 "@Q bra WL;\n\t"
                 "}" ::"r"(a), "r"(p), "r"(ok) : "memory");
}
__device__ __forceinline__ void mbar_wait_cluster(uint32_t a, uint32_t p) {
    asm volatile("{.reg .pred P, Q; .reg .u32 it;\n\t"
                 "mov.u32 it, 0;\n\t"
                 "WL: mbarrier.try_wait.parity.acquire.cluster.shared::cta.b64 P,[%0],%1;\n\t"
                 "add.u32 it, it, 1;\n\t"
                 "setp.lt.and.u32 Q, it, 100000, !P;\n\t"
                 "@Q bra WL;\n\t"
                 "}" ::"r"(a), "r"(p) : "memory");
}
__device__ __forceinline__ void cpasync16(uint32_t dst, const void* src) { asm volatile("cp.async.cg.shared.global [%0],[%1],16;" ::"r"(dst), "l"(src) : "memory"); }
__device__ __forceinline__ void cpasync16_pf(uint32_t dst, const void* src) { asm volatile("cp.async.cg.shared.global.L2::256B [%0],[%1],16;" ::"r"(dst), "l"(src) : "memory"); }
__device__ __forceinline__ void cpasync_arrive(uint32_t bar) { asm volatile("cp.async.mbarrier.arrive.noinc.shared::cta.b64 [%0];" ::"r"(bar) : "memory"); }
__device__ __forceinline__ uint32_t swz(uint32_t a) { return a ^ ((a >> 3) & 0x70); }
__device__ __forceinline__ void ldsm4(uint32_t* r, uint32_t a) {
    asm volatile("ldmatrix.sync.aligned.m8n8.x4.shared.b16 {%0,%1,%2,%3},[%4];" : "=r"(r[0]), "=r"(r[1]), "=r"(r[2]), "=r"(r[3]) : "r"(a) : "memory");
}
__device__ __forceinline__ void ldsm2t(uint32_t& r0, uint32_t& r1, uint32_t a) {
    asm volatile("ldmatrix.sync.aligned.m8n8.x2.trans.shared.b16 {%0,%1},[%2];" : "=r"(r0), "=r"(r1) : "r"(a) : "memory");
}
__device__ __forceinline__ void ldsm4t(uint32_t* r, uint32_t a) {
    asm volatile("ldmatrix.sync.aligned.m8n8.x4.trans.shared.b16 {%0,%1,%2,%3},[%4];" : "=r"(r[0]), "=r"(r[1]), "=r"(r[2]), "=r"(r[3]) : "r"(a) : "memory");
}
__device__ __forceinline__ void stsm4(uint32_t a, uint32_t r0, uint32_t r1, uint32_t r2, uint32_t r3) {
    asm volatile("stmatrix.sync.aligned.m8n8.x4.shared.b16 [%0],{%1,%2,%3,%4};" ::"r"(a), "r"(r0), "r"(r1), "r"(r2), "r"(r3) : "memory");
}
__device__ __forceinline__ void lds128(uint32_t* r, uint32_t a) {
    asm volatile("ld.shared.v4.u32 {%0,%1,%2,%3},[%4];" : "=r"(r[0]), "=r"(r[1]), "=r"(r[2]), "=r"(r[3]) : "r"(a) : "memory");
}
__device__ __forceinline__ uint32_t lds32(uint32_t a) { uint32_t r; asm volatile("ld.shared.u32 %0,[%1];" : "=r"(r) : "r"(a) : "memory"); return r; }
__device__ __forceinline__ void sts32(uint32_t a, uint32_t v) { asm volatile("st.shared.u32 [%0],%1;" ::"r"(a), "r"(v) : "memory"); }
__device__ __forceinline__ uint32_t pack_bf16(float lo, float hi) { uint32_t r; asm("cvt.rn.bf16x2.f32 %0,%1,%2;" : "=r"(r) : "f"(hi), "f"(lo)); return r; }
__device__ __forceinline__ uint32_t mul_bf16x2(uint32_t a, uint32_t b) { uint32_t r; asm volatile("mul.rn.bf16x2 %0,%1,%2;" : "=r"(r) : "r"(a), "r"(b)); return r; }
__device__ __forceinline__ uint32_t fma_bf16x2(uint32_t a, uint32_t b, uint32_t c) { uint32_t r; asm("fma.rn.bf16x2 %0,%1,%2,%3;" : "=r"(r) : "r"(a), "r"(b), "r"(c)); return r; }
__device__ __forceinline__ uint32_t add_bf16x2(uint32_t a, uint32_t b) { uint32_t r; asm volatile("add.rn.bf16x2 %0,%1,%2;" : "=r"(r) : "r"(a), "r"(b)); return r; }
__device__ __forceinline__ uint32_t vxor(uint32_t a, uint32_t b) { uint32_t r; asm volatile("xor.b32 %0,%1,%2;" : "=r"(r) : "r"(a), "r"(b)); return r; }
__device__ __forceinline__ uint32_t vprmt(uint32_t a, uint32_t b, uint32_t c) { uint32_t r; asm volatile("prmt.b32 %0,%1,%2,%3;" : "=r"(r) : "r"(a), "r"(b), "r"(c)); return r; }
__device__ __forceinline__ uint32_t vpack(float lo, float hi) { uint32_t r; asm volatile("cvt.rn.bf16x2.f32 %0,%1,%2;" : "=r"(r) : "f"(hi), "f"(lo)); return r; }
__device__ __forceinline__ float bf_lo(uint32_t x) { return __uint_as_float(x << 16); }
__device__ __forceinline__ float bf_hi(uint32_t x) { return __uint_as_float(x & 0xffff0000u); }
__device__ __forceinline__ float bfr(float x) { return __bfloat162float(__float2bfloat16_rn(x)); }
__device__ __forceinline__ float tanh_fast(float u) { float t; asm("tanh.approx.f32 %0,%1;" : "=f"(t) : "f"(u)); return t; }
__device__ __forceinline__ float ex2f(float u) { float t; asm("ex2.approx.ftz.f32 %0,%1;" : "=f"(t) : "f"(u)); return t; }
__device__ __forceinline__ float rcpf(float u) { float t; asm("rcp.approx.ftz.f32 %0,%1;" : "=f"(t) : "f"(u)); return t; }
__device__ __forceinline__ void wg_fence() { asm volatile("wgmma.fence.sync.aligned;" ::: "memory"); }
__device__ __forceinline__ void wg_commit() { asm volatile("wgmma.commit_group.sync.aligned;" ::: "memory"); }
template <int N> __device__ __forceinline__ void wg_wait() { asm volatile("wgmma.wait_group.sync.aligned %0;" ::"n"(N) : "memory"); }
template <int N> __device__ __forceinline__ void fence_regs(float* d) {
#pragma unroll
    for (int i = 0; i < N; i++) asm volatile("" : "+f"(d[i])::"memory");
}
__device__ __forceinline__ uint32_t uni(uint32_t x) { return __shfl_sync(0xffffffffu, x, 0); }
__device__ __forceinline__ void fence_async() { asm volatile("fence.proxy.async.shared::cta;" ::: "memory"); }
__device__ __forceinline__ void fence_acq_async() { if (PFENCE) fence_async(); else asm volatile("fence.proxy.async::generic.acquire.sync_restrict::shared::cluster.cluster;" ::: "memory"); }
__device__ __forceinline__ uint64_t mk64(uint32_t lo, uint32_t hi) { return ((uint64_t)hi << 32) | lo; }

#define D8(b) "+f"(d[b + 0]), "+f"(d[b + 1]), "+f"(d[b + 2]), "+f"(d[b + 3]), "+f"(d[b + 4]), "+f"(d[b + 5]), "+f"(d[b + 6]), "+f"(d[b + 7])
#define O8(b) "=f"(d[b + 0]), "=f"(d[b + 1]), "=f"(d[b + 2]), "=f"(d[b + 3]), "=f"(d[b + 4]), "=f"(d[b + 5]), "=f"(d[b + 6]), "=f"(d[b + 7])
#define L16 "{%0,%1,%2,%3,%4,%5,%6,%7,%8,%9,%10,%11,%12,%13,%14,%15}"
#define L32 "{%0,%1,%2,%3,%4,%5,%6,%7,%8,%9,%10,%11,%12,%13,%14,%15,%16,%17,%18,%19,%20,%21,%22,%23,%24,%25,%26,%27,%28,%29,%30,%31}"
#define L64 "{%0,%1,%2,%3,%4,%5,%6,%7,%8,%9,%10,%11,%12,%13,%14,%15,%16,%17,%18,%19,%20,%21,%22,%23,%24,%25,%26,%27,%28,%29,%30,%31,%32,%33,%34,%35,%36,%37,%38,%39,%40,%41,%42,%43,%44,%45,%46,%47,%48,%49,%50,%51,%52,%53,%54,%55,%56,%57,%58,%59,%60,%61,%62,%63}"

#define DSC_PRE(B, O, H) "{.reg .b32 lo; .reg .b64 dsc; add.u32 lo, " B ", " O "; mov.b64 dsc, {lo, " H "}; "
template <uint32_t OFF, uint32_t HI> __device__ __forceinline__ void wg128_tb(float* d, const uint32_t* a, uint32_t base) {
    asm volatile(DSC_PRE("%68", "%69", "%70") "wgmma.mma_async.sync.aligned.m64n128k16.f32.bf16.bf16 " L64 ", {%64,%65,%66,%67}, dsc, 1,1,1,1;}"
                 : D8(0), D8(8), D8(16), D8(24), D8(32), D8(40), D8(48), D8(56)
                 : "r"(a[0]), "r"(a[1]), "r"(a[2]), "r"(a[3]), "r"(base), "n"(OFF), "n"(HI));
}
template <bool ACC, uint32_t OFF, uint32_t HI> __device__ __forceinline__ void wg64(float* d, const uint32_t* a, uint32_t base) {
    if (ACC)
        asm volatile(DSC_PRE("%36", "%37", "%38") "wgmma.mma_async.sync.aligned.m64n64k16.f32.bf16.bf16 " L32 ", {%32,%33,%34,%35}, dsc, 1,1,1,0;}"
                     : D8(0), D8(8), D8(16), D8(24) : "r"(a[0]), "r"(a[1]), "r"(a[2]), "r"(a[3]), "r"(base), "n"(OFF), "n"(HI));
    else
        asm volatile(DSC_PRE("%36", "%37", "%38") "wgmma.mma_async.sync.aligned.m64n64k16.f32.bf16.bf16 " L32 ", {%32,%33,%34,%35}, dsc, 0,1,1,0;}"
                     : O8(0), O8(8), O8(16), O8(24) : "r"(a[0]), "r"(a[1]), "r"(a[2]), "r"(a[3]), "r"(base), "n"(OFF), "n"(HI));
}
template <bool ACC, uint32_t OFF, uint32_t HI> __device__ __forceinline__ void wg32(float* d, const uint32_t* a, uint32_t base) {
    if (ACC)
        asm volatile(DSC_PRE("%20", "%21", "%22") "wgmma.mma_async.sync.aligned.m64n32k16.f32.bf16.bf16 " L16 ", {%16,%17,%18,%19}, dsc, 1,1,1,0;}"
                     : D8(0), D8(8) : "r"(a[0]), "r"(a[1]), "r"(a[2]), "r"(a[3]), "r"(base), "n"(OFF), "n"(HI));
    else
        asm volatile(DSC_PRE("%20", "%21", "%22") "wgmma.mma_async.sync.aligned.m64n32k16.f32.bf16.bf16 " L16 ", {%16,%17,%18,%19}, dsc, 0,1,1,0;}"
                     : O8(0), O8(8) : "r"(a[0]), "r"(a[1]), "r"(a[2]), "r"(a[3]), "r"(base), "n"(OFF), "n"(HI));
}
template <bool ACC, bool PERS, uint32_t OFF>
__device__ __forceinline__ void wgsp32(float* d, uint32_t a0, uint32_t a1, uint32_t a2, uint32_t a3, uint32_t base, uint32_t meta) {
    if (PERS) {
        const uint64_t dsc = mk64(base + OFF, 128 >> 4);
        if (ACC)
            asm volatile("wgmma.mma_async.sp.sync.aligned.m64n32k32.f32.bf16.bf16 " L16 ", {%16,%17,%18,%19}, %20, %21, 0, 1,1,1,0;"
                         : D8(0), D8(8) : "r"(a0), "r"(a1), "r"(a2), "r"(a3), "l"(dsc), "r"(meta));
        else
            asm volatile("wgmma.mma_async.sp.sync.aligned.m64n32k32.f32.bf16.bf16 " L16 ", {%16,%17,%18,%19}, %20, %21, 0, 0,1,1,0;"
                         : O8(0), O8(8) : "r"(a0), "r"(a1), "r"(a2), "r"(a3), "l"(dsc), "r"(meta));
    } else {
        if (ACC)
            asm volatile(DSC_PRE("%20", "%22", "8") "wgmma.mma_async.sp.sync.aligned.m64n32k32.f32.bf16.bf16 " L16 ", {%16,%17,%18,%19}, dsc, %21, 0, 1,1,1,0;}"
                         : D8(0), D8(8) : "r"(a0), "r"(a1), "r"(a2), "r"(a3), "r"(base), "r"(meta), "n"(OFF));
        else
            asm volatile(DSC_PRE("%20", "%22", "8") "wgmma.mma_async.sp.sync.aligned.m64n32k32.f32.bf16.bf16 " L16 ", {%16,%17,%18,%19}, dsc, %21, 0, 0,1,1,0;}"
                         : O8(0), O8(8) : "r"(a0), "r"(a1), "r"(a2), "r"(a3), "r"(base), "r"(meta), "n"(OFF));
    }
}

__host__ __device__ constexpr uint32_t w1_off(int j, int g) { return OFF_P0 + 4096 + ((3 - j) % 3) * 32768 + g * 16384; }

template <bool PF>
__device__ __forceinline__ void gather_tile(uint32_t dst_tile, const uint32_t* off8, const char* tb, int lane) {
    const uint32_t x = dst_tile + (lane >> 3) * 128 + (lane & 7) * 16;
    const uint32_t x0 = swz(x), x1 = swz(x + 512);
#pragma unroll
    for (int i = 0; i < 8; i++) {
        const uint32_t dst = ((i & 1) ? x1 : x0) + (i >> 1) * 1024;
        if (PF) cpasync16_pf(dst, tb + off8[i]); else cpasync16(dst, tb + off8[i]);
    }
}

template <bool ACC, uint32_t HI> __device__ __forceinline__ void wg16(float* d, uint32_t a0, uint32_t a1, uint32_t a2, uint32_t a3, uint32_t lo) {
    if (ACC)
        asm volatile("{.reg .b64 dsc; mov.b64 dsc, {%12, %13}; wgmma.mma_async.sync.aligned.m64n16k16.f32.bf16.bf16 {%0,%1,%2,%3,%4,%5,%6,%7}, {%8,%9,%10,%11}, dsc, 1,1,1,0;}"
                     : D8(0) : "r"(a0), "r"(a1), "r"(a2), "r"(a3), "r"(lo), "n"(HI));
    else
        asm volatile("{.reg .b64 dsc; mov.b64 dsc, {%12, %13}; wgmma.mma_async.sync.aligned.m64n16k16.f32.bf16.bf16 {%0,%1,%2,%3,%4,%5,%6,%7}, {%8,%9,%10,%11}, dsc, 0,1,1,0;}"
                     : O8(0) : "r"(a0), "r"(a1), "r"(a2), "r"(a3), "r"(lo), "n"(HI));
}
template <bool FIRST, int O, uint32_t OFF>
__device__ __forceinline__ void half64(float* acc, const uint32_t* wf, uint32_t base) {
    constexpr uint32_t hi = (S_TILE >> 4) | (1u << 30);
    constexpr uint32_t lo = ((OFF >> 4) + O * 64) | (1u << 16);
    wg64<!FIRST, lo, hi>(acc, wf, base);
    wg64<true, lo + 2, hi>(acc, wf + 4, base);
    wg64<true, lo + 4, hi>(acc, wf + 8, base);
    wg64<true, lo + 6, hi>(acc, wf + 12, base);
}
template <bool FIRST, uint32_t OFF>
__device__ __forceinline__ void half32(float* acc, const uint32_t* wf, uint32_t base) {
    constexpr uint32_t hi = (1024 >> 4) | (1u << 30);
    constexpr uint32_t lo = (OFF >> 4) | (1u << 16);
    wg32<!FIRST, lo, hi>(acc, wf, base);
    wg32<true, lo + 2, hi>(acc, wf + 4, base);
    wg32<true, lo + 4, hi>(acc, wf + 8, base);
    wg32<true, lo + 6, hi>(acc, wf + 12, base);
}
template <int C0> __device__ __forceinline__ void store_half64(const float* acc, uint32_t stb) {
#pragma unroll
    for (int c = C0; c < C0 + 4; c += 2)
        stsm4(stb ^ (c << 4), pack_bf16(acc[4 * c], acc[4 * c + 1]), pack_bf16(acc[4 * c + 2], acc[4 * c + 3]),
              pack_bf16(acc[4 * c + 4], acc[4 * c + 5]), pack_bf16(acc[4 * c + 6], acc[4 * c + 7]));
}
__device__ __forceinline__ void ldg128(uint32_t* r, const char* p) {
    asm volatile("ld.global.v4.u32 {%0,%1,%2,%3},[%4];" : "=r"(r[0]), "=r"(r[1]), "=r"(r[2]), "=r"(r[3]) : "l"(p) : "memory");
}
__device__ __forceinline__ void mbar_arrive2(uint32_t a) { asm volatile("mbarrier.arrive.shared::cta.b64 _, [%0], 2;" ::"r"(a) : "memory"); }
__device__ __forceinline__ void arrive_if(uint32_t a, bool on) {
    asm volatile("{.reg .pred P; setp.ne.u32 P, %1, 0; @P mbarrier.arrive.shared::cta.b64 _, [%0];}" ::"r"(a), "r"((uint32_t)on) : "memory");
}
__device__ __forceinline__ void arrive_cluster(uint32_t a) { asm volatile("mbarrier.arrive.relaxed.cluster.shared::cluster.b64 _,[%0];" ::"r"(a) : "memory"); }
__device__ __forceinline__ uint32_t mapa(uint32_t a, uint32_t r) { uint32_t x; asm("mapa.shared::cluster.u32 %0,%1,%2;" : "=r"(x) : "r"(a), "r"(r)); return x; }
__device__ __forceinline__ int tid_again() { int t; asm volatile("mov.u32 %0, %%tid.x;" : "=r"(t)); return t; }

__global__ void __cluster_dims__(2, 1, 1) __launch_bounds__(384, 1)
fib_kernel(const int* __restrict__ idx, const char* __restrict__ table, const char* __restrict__ wc, const char* __restrict__ w1g,
           const unsigned short* __restrict__ wbi, const __nv_bfloat16* __restrict__ wd2,
           const __grid_constant__ CUtensorMap tmW1,
           const unsigned short* __restrict__ se1, const unsigned short* __restrict__ se2, __nv_bfloat16* __restrict__ out) {
    extern __shared__ __align__(1024) char sm[];
    const uint32_t t_al = clock();
    const uint32_t sb = smem_u32(sm);
    const uint32_t bar = sb + OFF_BAR;
    const int tid = threadIdx.x, lane = tid & 31;
    const uint32_t c = blockIdx.x & 1;
    const int own0 = blockIdx.x * 32, peer0 = own0 ^ 32;

    if (tid < 192) {
        const int n = tid >> 6;
        const bool own = (tid & 32) != 0;
        const int* ip = idx + ((own ? own0 : peer0) + (lane >> 3)) * 26 + n;
        uint32_t o8[8];
#pragma unroll
        for (int i = 0; i < 8; i++) o8[i] = (uint32_t)__ldg(ip + i * 104) << 8;
        if (n) {
            const uint32_t x = sb + OFF_L + 22 * S_TILE + (tid - 64) * 16;
            const char* src = (const char*)wbi + (((tid - 64) >> 3) * 256 + c * 128 + (tid & 7) * 16);
#pragma unroll
            for (int k = 0; k < 8; k++) cpasync16(swz(x + (k >> 1) * S_TILE) + (k & 1) * 2048, src + k * 4096);
            if (tid < 96) cpasync16(sb + OFF_W2 + lane * 16, (const char*)wd2 + lane * 16);
            asm volatile("cp.async.commit_group;" ::: "memory");
            asm volatile("bar.sync 0, 384;" ::: "memory");
            if (PP) while ((uint32_t)clock() - t_al < PT0 + n * PP) {}
        }
        gather_tile<false>(sb + (own ? OFF_L + n * S_TILE : peer_off(n)), o8, table + c * 128 + (lane & 7) * 16, lane);
        if (own) gather_tile<false>(sb + OFF_L + (10 + n) * S_TILE, o8, table + (c ^ 1) * 128 + (lane & 7) * 16, lane);
        if (tid == 0) STAMP(0);
        if (!n) asm volatile("bar.sync 0, 384;" ::: "memory");
        cpasync_arrive(bar + 8 * B_AF + 8 * n);
    }
    const int warp = __shfl_sync(0xffffffffu, tid >> 5, 0);
    if (warp >= 6) {
        if (warp == 9 || warp == 10) {
            const int2* ip = (const int2*)(idx + ((warp == 9 ? own0 : peer0) + lane) * 26);
            int2 v[13];
#pragma unroll
            for (int i = 0; i < 13; i++) v[i] = __ldg(ip + i);
            asm volatile("bar.arrive 0, 384;" ::: "memory");
            const uint32_t ia = sb + (warp == 9 ? OFF_IDX : OFF_PIDX) + ((lane & 3) * 8 + (lane >> 2)) * 4;
#pragma unroll
            for (int i = 0; i < 13; i++) { sts32(ia + i * 256, (uint32_t)v[i].x << 8); sts32(ia + i * 256 + 128, (uint32_t)v[i].y << 8); }
        } else if (lane == 0) {
            if (W1PF && warp < 8) {
#pragma unroll
                for (int u = 0; u < W1PF; u++)
                    asm volatile("cp.async.bulk.prefetch.L2.global [%0], 512;" ::"l"(w1g + ((1 + warp - 6 + 2 * u) * 65536 + blockIdx.x * 512)) : "memory");
            }
            const int q = (warp == 11) ? 3 : warp - 6;
            const uint32_t c0 = (0x04084040u >> (8 * q)) & 255, c1 = (0x80010840u >> (8 * q)) & 255, c2 = (0x18010840u >> (8 * q)) & 255;
#pragma unroll
            for (int i = 0; i < 8; i++) {
                mbar_init(bar + 192 * q + 8 * i, c0); mbar_init(bar + 192 * q + 64 + 8 * i, c1); mbar_init(bar + 192 * q + 128 + 8 * i, c2);
            }
            if (warp == 8) {
#pragma unroll
                for (int i = 0; i < 6; i++) mbar_expect(bar + 8 * (B_W1F + i), 16384);
                mbar_expect(bar + 8 * B_HX, 10240);
                mbar_expect(bar + 8 * (B_HX + 1), 10240);
#pragma unroll
                for (int u = 0; u < 2 * W1PRE; u++)
                    asm volatile("cp.async.bulk.tensor.3d.shared::cluster.global.mbarrier::complete_tx::bytes [%0],[%1,{%3,%4,%5}],[%2];"
                                 ::"r"(sb + w1_off(u >> 1, u & 1)), "l"(&tmW1), "r"(bar + 8 * (B_W1F + (u & 1) * 3 + (u >> 1))), "r"(0),
                                 "r"((int)(c * 64 + (u >> 1) * 128)), "r"(2 * (u & 1)) : "memory");
            }
            asm volatile("fence.mbarrier_init.release.cluster;" ::: "memory");
        }
        if (warp < 8) {
            const uint32_t one = (tid == 192 + 15) ? 0x3F803F80u : 0u;
#pragma unroll
            for (int i = 0; i < 5; i++) {
                const int e = tid - 288 + 64 * i;
                const uint32_t o = (e < 0) ? OFF_SEL + 512 + e * 16 : OFF_L + (e >> 3) * S_TILE + 4096 + (e & 7) * 16;
                const uint32_t x = (i == 1) ? one : 0u;
                if (e < 208) *(uint4*)(sm + o) = make_uint4(x, x, x, x);
            }
            fence_async();
        }
        __syncwarp();
        if (warp != 9 && warp != 10) asm volatile("bar.arrive 0, 384;" ::: "memory");
        asm volatile("bar.sync 4, 192;" ::: "memory");
    }
    asm volatile("barrier.cluster.arrive.relaxed.aligned;" ::: "memory");

    if (warp >= 8) {
        asm volatile("setmaxnreg.dec.sync.aligned.u32 40;");
        if (warp == 8) {
            const char* pf = w1g + (3 * 65536 + blockIdx.x * 512);
            uint32_t ph = 1;
            int row = c * 64;
#pragma unroll 1
            for (int s0 = 0; s0 < 27; s0 += 3) {
#pragma unroll
                for (int j = 0; j < 3; j++) {
                    if (j == 2 && s0 == 24) break;
                    if (j >= W1PRE || s0) {
#pragma unroll
                        for (int g = 0; g < 2; g++) {
                            mbar_wait(bar + 8 * (B_W1E + 3 * g + j), ph);
                            asm volatile("{.reg .pred P; elect.sync _|P,0xffffffff;"
                                         " @P cp.async.bulk.tensor.3d.shared::cluster.global.mbarrier::complete_tx::bytes [%0],[%1,{%3,%4,%5}],[%2];}"
                                         ::"r"(sb + w1_off(j, g)), "l"(&tmW1), "r"(bar + 8 * (B_W1F + 3 * g + j)), "r"(0), "r"(row), "r"(2 * g) : "memory");
                        }
                    }
                    if (s0 + j < 23)
                        asm volatile("{.reg .pred P; elect.sync _|P,0xffffffff; @P cp.async.bulk.prefetch.L2.global [%0], 512;}" ::"l"(pf) : "memory");
                    pf += 65536; row += 128;
                }
                ph ^= 1;
            }
            mbar_wait(bar + 8 * B_PREP, 0);
            asm volatile("fence.proxy.async.global;" ::: "memory");
            asm volatile("{.reg .pred P; elect.sync _|P,0xffffffff; @P mbarrier.arrive.shared::cta.b64 _, [%2], 7; @P mbarrier.arrive.expect_tx.shared::cta.b64 _, [%2], 2048;"
                         " @P cp.async.bulk.shared::cluster.global.mbarrier::complete_tx::bytes [%0],[%1],2048,[%2];}"
                         ::"r"(sb + OFF_SE), "l"(g_se), "r"(bar + 8 * B_SEF) : "memory");
        } else {
            const uint32_t ib = sb + OFF_IDX + (lane >> 3) * 32;
            uint32_t o8[8];
            if (warp < 11) {
                const char* tb = table + c * 128 + (lane & 7) * 16;
                if (warp == 9) {
#pragma unroll 1
                    for (int n = 3; n < 26; n++) {
                        lds128(o8, ib + n * 128); lds128(o8 + 4, ib + n * 128 + 16);
                        const uint32_t o = lds32(sb + OFF_IDX + n * 128 + lane * 4);
                        if (n >= RAMP) mbar_wait(bar + 8 * B_AF + 8 * (n - RAMP), 0);
                        if (PP && n < PN) while ((uint32_t)clock() - t_al < PT0 + n * PP) __nanosleep(20);
                        gather_tile<false>(sb + OFF_L + n * S_TILE, o8, tb, lane);
                        if (n < 8) gather_tile<false>(sb + OFF_L + (10 + n) * S_TILE, o8, tb + (c ? -128 : 128), lane);
                        else asm volatile("prefetch.global.L2 [%0];" ::"l"(table + (c ^ 1) * 128 + o));
                        cpasync_arrive(bar + 8 * B_AF + 8 * n);
                    }
                } else {
                    int j = 0; uint32_t ph = 0;
#pragma unroll 1
                    for (int n = 3; n < 26; n++) {
                        lds128(o8, ib + 3328 + n * 128); lds128(o8 + 4, ib + 3328 + n * 128 + 16);
                        mbar_wait(bar + 8 * B_AE + 8 * j, ph);
                        gather_tile<false>(sb + peer_off(j), o8, tb, lane);
                        cpasync_arrive(bar + 8 * B_AF + 8 * n);
                        if (++j == 3) { j = 0; ph ^= 1; }
                    }
                }
            } else {
                const int b = blockIdx.x;
                uint32_t wt0, wt1;
                {
                    const int it = b * 16 + (lane >> 1);
                    const int ch = it >> 10, s = (it >> 7) & 7, th = it & 127;
                    const int e = ch * 64 + (th >> 5) * 16 + ((th & 31) >> 2), d = 16 * s + 2 * (th & 3) + 8 * (lane & 1);
                    const unsigned short* p = wbi + d * 128 + e;
                    wt0 = __ldg(p) | ((uint32_t)__ldg(p + 128) << 16);
                    wt1 = __ldg(p + 8) | ((uint32_t)__ldg(p + 136) << 16);
                }
                if (b < 112) {
                    const int kc = b >> 4, ng = (b >> 2) & 3, eo = (b & 3) * 4 + (lane >> 3), nr = lane & 7;
                    const int n = ng * 8 + nr;
                    const int j = (n < 24) ? n : ((n == 24) ? 24 : (n == 26) ? 25 : -1);
#pragma unroll
                    for (int ii = 0; ii < 4; ii++)
                        if (j >= 0 && 4 * kc + ii < 26) asm volatile("prefetch.global.L2 [%0];" ::"l"(wc + (uint32_t)(((26 + 4 * kc + ii) * 26 + j) * 256 + eo * 16)));
#pragma unroll 1
                    for (int pq = 0; pq < 2 && n <= 26; pq++) {
                        uint4 r[4];
#pragma unroll
                        for (int ii = 0; ii < 4; ii++) {
                            const int i = 4 * kc + ii;
                            r[ii] = make_uint4(0, 0, 0, 0);
                            if (j >= 0 && i < 26) r[ii] = __ldg((const uint4*)(wc + (uint32_t)(((pq * 26 + i) * 26 + j) * 256 + eo * 16)));
                        }
                        uint4* dst = g_wc + (uint32_t)(((eo >> 3) * 32 + (eo & 3) * 8 + ((eo >> 2) & 1)) * (WC_STAGE / 16) + pq * (WC_TILE / 16) + kc * (WC_LBO / 16) + ng * 8 + nr);
                        dst[0 * (WC_STAGE / 8)] = make_uint4(__byte_perm(r[0].x, r[1].x, 0x5410), __byte_perm(r[0].x, r[1].x, 0x7632), __byte_perm(r[2].x, r[3].x, 0x5410), __byte_perm(r[2].x, r[3].x, 0x7632));
                        dst[1 * (WC_STAGE / 8)] = make_uint4(__byte_perm(r[0].y, r[1].y, 0x5410), __byte_perm(r[0].y, r[1].y, 0x7632), __byte_perm(r[2].y, r[3].y, 0x5410), __byte_perm(r[2].y, r[3].y, 0x7632));
                        dst[2 * (WC_STAGE / 8)] = make_uint4(__byte_perm(r[0].z, r[1].z, 0x5410), __byte_perm(r[0].z, r[1].z, 0x7632), __byte_perm(r[2].z, r[3].z, 0x5410), __byte_perm(r[2].z, r[3].z, 0x7632));
                        dst[3 * (WC_STAGE / 8)] = make_uint4(__byte_perm(r[0].w, r[1].w, 0x5410), __byte_perm(r[0].w, r[1].w, 0x7632), __byte_perm(r[2].w, r[3].w, 0x5410), __byte_perm(r[2].w, r[3].w, 0x7632));
                    }
                } else {
                    const int q = b - 112, g = lane >> 2, t = lane & 3;
                    uint32_t lo = 0, hi = 0;
                    if (q < 8) {
                        const int f = 2 * (8 * (q >> 2) + 2 * t + ((q >> 1) & 1)), r = 8 * (q & 1) + g;
                        if (f < 26 && r < 13) { lo = __ldg(se1 + f * 13 + r); hi = __ldg(se1 + f * 13 + 13 + r); }
                    } else {
                        const int r = 8 * ((q - 8) >> 2) + 2 * t, f = 8 * (q & 3) + g;
                        if (f < 26 && r < 13) lo = __ldg(se2 + r * 26 + f);
                        if (f < 26 && r < 12) hi = __ldg(se2 + r * 26 + 26 + f);
                    }
                    ((uint32_t*)g_se)[q * 32 + lane] = lo | (hi << 16);
                }
                ((uint2*)g_wt)[b * 32 + lane] = make_uint2(wt0, wt1);
                __threadfence();
                asm volatile("fence.proxy.async.global;" ::: "memory");
                __syncwarp();
                if (lane == 0) {
                    const unsigned tk = atomicAdd(&g_cnt, 1u);
                    const unsigned target = (tk & ~127u) + 128u;
                    unsigned cur; int it = 0;
#pragma unroll 1
                    do {
                        asm volatile("ld.acquire.gpu.global.u32 %0,[%1];" : "=r"(cur) : "l"(&g_cnt) : "memory");
                        if ((int)(cur - target) >= 0) break;
                        __nanosleep(200);
                    } while (++it < 100000);
                    asm volatile("mbarrier.arrive.shared::cta.b64 _, [%0], 8;" ::"r"(bar + 8 * B_PREP) : "memory");
                    STAMP(3);
                }
                __syncwarp();
            }
        }
        __syncwarp();
        asm volatile("barrier.cluster.wait.aligned;" ::: "memory");
        asm volatile("fence.proxy.async.global;" ::: "memory");
        {
            const uint32_t ib = sb + OFF_IDX + (lane >> 3) * 32;
            const char* tb = table + (c ^ 1) * 128 + (lane & 7) * 16;
            const int wq = (warp - 9) & 3;
            uint32_t o8[8];
#pragma unroll 1
            for (int wave = 0; wave < 2; wave++) {
#pragma unroll 1
                for (int f0 = 8 + wq; f0 < 26 - 2 * wave; f0 += 4) {
                    const int f = (f0 < 16 && !wave) ? f0 ^ 4 : f0;
                    lds128(o8, ib + f * 128); lds128(o8 + 4, ib + f * 128 + 16);
                    const uint32_t wb = wave ? (f < 16 ? B_TD + (f - 7) / 3 : B_GD + 4) : (f >= 24 ? B_FR2 : (f == 8 || f >= 16) ? B_FR1 : B_FR0);
                    const uint32_t dst = (f < 16) ? OFF_A : (f < 24) ? (wave ? OFF_L : OFF_A) - 16 * S_TILE : OFF_X - 24 * S_TILE;
                    mbar_wait(bar + 8 * wb, 0);
                    if (tid == 288) STAMP(64 + wave * 16 + (f >> 1));
                    gather_tile<false>(sb + dst + f * S_TILE, o8, tb, lane);
                    if (f0 & 4) cpasync_arrive(bar + 8 * B_RF + 32 * wave + 8 * (f >> 3));
                    if (tid == 288) STAMP(65 + wave * 16 + (f >> 1));
                }
                cpasync_arrive(bar + 8 * (B_RF + 3) + 32 * wave);
                if (wq >= 2) {
                    const uint32_t g = warp & 1;
                    const uint32_t dstw = sb + (wave ? OFF_L + 8 * S_TILE : OFF_B) + g * WC_STAGE;
                    const char* src = (const char*)g_wc + (((c ^ wave) * 32 + g) * WC_STAGE);
#pragma unroll 1
                    for (int u = 0; u < 4; u++) {
#pragma unroll
                        for (int h = 0; h < 4; h++) {
                            mbar_wait(bar + 8 * (B_WCE + h) + 32 * g, u & 1);
                            asm volatile("{.reg .pred P; elect.sync _|P,0xffffffff; @P mbarrier.arrive.expect_tx.shared::cta.b64 _, [%2], 6048;"
                                         " @P cp.async.bulk.shared::cluster.global.mbarrier::complete_tx::bytes [%0],[%1],6048,[%2];}"
                                         ::"r"(dstw + wc_slot(h)), "l"(src + h * 2 * WC_STAGE), "r"(bar + 8 * (B_WCF + h) + 32 * g) : "memory");
                        }
                        src += 8 * WC_STAGE;
                    }
                } else if (wave == 0) {
                    mbar_wait(bar + 8 * (B_GD + 2), 0);
#pragma unroll 1
                    for (int f = wq; f < 8; f += 2) {
                        if (RSL) __nanosleep(RSL);
                        lds128(o8, ib + f * 128); lds128(o8 + 4, ib + f * 128 + 16);
                        gather_tile<false>(sb + OFF_A + f * S_TILE, o8, tb, lane);
                    }
                    cpasync_arrive(bar + 8 * (B_RF + 4));
                    cpasync_arrive(bar + 8 * (B_RF + 4));
                }
            }
            asm volatile("cp.async.wait_all;" ::: "memory");
        }
    } else {
        asm volatile("setmaxnreg.inc.sync.aligned.u32 232;");
        const int wg = warp >> 2;
        const bool el = (lane == 0);
        const uint32_t sbm = (sb & 0x3FFFF) >> 4;
        const uint32_t cb = sbm + wg * 128;
        const uint32_t c3 = sbm + wg * (S_TILE >> 4);
        uint32_t wf[32], H[3][32], ai[4];
        float accA[32], accB[32];

#define WC_RELEASE2(S, ON, DEP) arrive_if(bar + 8 * (B_WCE + (S)) + (tid2 & 1) * 8 + (tid2 & 2) * 16 + (DEP), (tid2 & 31) < 4 && (ON));
#define EW_STEP(W, G, ENTRY, FC, PC, FN, PN, HOOKP, HOOK0, HOOK1, HOOK2, HOOK3)                                                  \
        {                                                                                                   \
            wg_fence();                                                                                     \
            if ((ENTRY) == 0) half64<true, 1, 0>(accB, wf, cb + ((FC) >> 4));                               \
            if ((ENTRY) == 1) half64<false, 1, 0>(accB, wf + 16, cb + ((PC) >> 4));                         \
            if ((ENTRY) == 2) half64<false, 1, 0>(accB, wf, cb + ((FC) >> 4));                              \
            wg_commit();                                                                                    \
            HOOK0                                                                                           \
            mbar_wait(bar + 8 * B_SB, ((G) + 1) & 1);                                            \
            if ((G) < 2 || !BE) wg_wait<1>();                                                  \
            fence_regs<32>(accA);                                                                           \
            store_half64<0>(accA, stb);                                                                     \
            if ((ENTRY) == 0) { wg_fence(); half64<false, 1, 0>(accB, wf + 16, cb + ((PC) >> 4)); wg_commit(); }              \
            store_half64<4>(accA, stb);                                                                     \
            { mbar_wait(bar + 8 * (B_RF + (G) + 1) + 32 * (W), 0); fence_acq_async(); } \
            HOOK1                                                                                           \
            wg_fence();                                                                                     \
            if ((G) < 2) half64<true, 0, 0>(accA, wf, cb + ((FN) >> 4)); else half32<true, 0>(accA, wf, c3 + ((FN) >> 4));            \
            wg_commit();                                                                                    \
            wg_wait<1>();                                                                                   \
            fence_regs<32>(accB);                                                                           \
            if ((G) == 1) WC_RELEASE2(0, true, 0)                                                   \
            if ((G) == 2) { if (el) mbar_arrive(bar + 8 * (B_GD + 2) + 32 * (W)); WC_RELEASE2(2, (W) != 0, 0) } \
            store_half64<0>(accB, stb + 8192);                                                              \
            if ((G) < 2) half64<false, 0, 0>(accA, wf + 16, cb + ((PN) >> 4)); else half32<false, 0>(accA, wf + 16, c3 + ((PN) >> 4)); \
            wg_commit();                                                                                    \
            store_half64<4>(accB, stb + 8192);                                                              \
            HOOK2                                                                                           \
            if ((G) < 2) {                                                                                  \
                asm volatile("bar.sync 1, 256;" ::: "memory");                                              \
                HOOKP                                                                                       \
                if ((G) == 1 && BE) { wg_fence(); half64<true, 1, 0>(accB, wf, cb + ((FN) >> 4)); wg_commit(); }  \
                _Pragma("unroll") for (int k = 0; k < 16; k++)                                              \
                    ldsm2t(H[(G) & 1][2 * k], H[(G) & 1][2 * k + 1], (ldb ^ ((2 * k & 6) << 4)) + k * 256); \
                if (el) mbar_arrive(bar + 8 * B_SB);                                                        \
            }                                                                                               \
            HOOK3                                                                                           \
            if (tid0) STAMP(36 + (W) * 8 + G);                                                              \
        }

        {
            const int w = warp & 3, t = lane & 3, mm = lane >> 3, rr = lane & 7;
            const bool tid0 = (tid == 0);
            const int tid2 = tid;
            float d[64], zacc[8];
#pragma unroll
            for (int i = 0; i < 64; i++) d[i] = 0.f;
#pragma unroll
            for (int i = 0; i < 8; i++) zacc[i] = 0.f;
            fence_regs<64>(d); fence_regs<8>(zacc);
            uint32_t h0c[32];
            {
                constexpr uint32_t WS = OFF_L + 22 * S_TILE;
                asm volatile("cp.async.wait_group 0;" ::: "memory");
                asm volatile("bar.sync 1, 256;" ::: "memory");
#pragma unroll
                for (int k = 0; k < 8; k++)
                    ldsm4t(wf + 4 * k, swz(sb + WS + (((k >> 1) ^ 2 ^ (2 * c)) * S_TILE) + ((k & 1) * 16 + (mm >> 1) * 8 + rr) * 128 + (2 * w + (mm & 1)) * 16));
            }
            {
                uint32_t a[2][16];
                const bool el0 = (tid & 127) == 0;
                const uint32_t zr = lds32(sb + OFF_SEL + (lane & 1) * 4);
                const uint32_t bid = 2 + wg + lds32(sb + OFF_SEL);
                const bool ispeer = (mm & 1) != 0;
                uint32_t abase = (ispeer ? sb + OFF_P0 : sb + OFF_L) + (w * 8 + rr) * 128 + (mm >> 1) * 16;
                constexpr uint32_t dhi = (1024 >> 4) | (1u << 30);
                const uint32_t wd0 = sbm + wg * 1024;
                uint32_t zd = sbm + ((OFF_SEL + 240) >> 4);
                const uint32_t bF = bar + 8 * B_W1F + wg * 24;
                mbar_wait(bar + 8 * B_AF, 0);
                if (tid0) STAMP(2);
                {
                    const uint32_t x = swz(abase);
#pragma unroll
                    for (int k = 0; k < 4; k++) ldsm4(&a[0][4 * k], x ^ (k * 32));
                    if (el) mbar_arrive(bar + 8 * B_AE + ((a[0][1] | a[0][5] | a[0][9] | a[0][13]) & zr));
                }
                mbar_wait(bF, 0);
                if (wg) asm volatile("bar.sync 3, 256;" ::: "memory");
                else while ((uint32_t)clock() - t_al < AL0) {}
                float acc0[16];
                constexpr uint32_t SCR0 = OFF_L + 18 * S_TILE;
                const uint32_t st0 = sb + SCR0 + (mm >> 1) * 8192 + (16 * w + 8 * (mm & 1) + rr) * 128 + ((wg ^ rr) << 4);
#define P1_ST0(F)                                                                                    \
                    {                                                                                \
                        fence_regs<16>(acc0);                                                        \
                        stsm4(st0 ^ ((F) << 4), pack_bf16(acc0[0], acc0[1]), pack_bf16(acc0[2], acc0[3]), pack_bf16(acc0[4], acc0[5]), pack_bf16(acc0[6], acc0[7])); \
                        stsm4((st0 ^ ((F) << 4)) + 16384, pack_bf16(acc0[8], acc0[9]), pack_bf16(acc0[10], acc0[11]), pack_bf16(acc0[12], acc0[13]), pack_bf16(acc0[14], acc0[15])); \
                    }
#define P1_STEP(q)                                                                                   \
                    {                                                                                \
                        constexpr int j = (q) % 3, jn = ((q) + 1) % 3;                               \
                        constexpr uint32_t nph = (((q) + 1) / 3) & 1;                                \
                        constexpr uint32_t dlo = (w1_off(j, 0) >> 4) | ((8192 >> 4) << 16);          \
                        const uint32_t* aa = a[(q) & 1];                                             \
                        if (wg == ((q) & 1)) {                                                       \
                            wg_fence();                                                              \
                            _Pragma("unroll") for (int k = 0; k < 4; k++)                            \
                                wg16<true, (128 >> 4)>(zacc, aa[4 * k], aa[4 * k + 1], aa[4 * k + 2], aa[4 * k + 3], zd); \
                            zd -= 1;                                                                 \
                        }                                                                            \
                        wg_fence();                                                                  \
                        if ((q) < 8 && ((q) & 1)) {                                                  \
                            fence_acq_async();                                                       \
                            half32<true, OFF_L + (9 + (q)) * S_TILE>(acc0, wf, c3);                  \
                            half32<false, OFF_L + ((q) & 6) * S_TILE>(acc0, wf + 16, c3);            \
                        }                                                                            \
                        wg128_tb<dlo, dhi>(d, aa, wd0);                                              \
                        wg128_tb<dlo + 128, dhi>(d, aa + 4, wd0);                                    \
                        wg128_tb<dlo + 256, dhi>(d, aa + 8, wd0);                                    \
                        wg128_tb<dlo + 384, dhi>(d, aa + 12, wd0);                                   \
                        wg_commit();                                                                 \
                        asm volatile("bar.arrive %0, 256;" ::"r"(bid ^ 1) : "memory");               \
                        if (AEPOS == 2 && (q) > 0 && el) mbar_arrive(bar + 8 * (B_AE + j));          \
                        if ((q) == 13 && s0 == 12) break;                                            \
                        if ((q) == 2 || (q) == 4 || (q) == 6) P1_ST0(((q) - 2) & 7)                        \
                        abase += ispeer ? peer_off(jn) - peer_off(j) : S_TILE;                                          \
                        const uint32_t x = swz(abase);                                               \
                        mbar_wait(bar + 8 * B_AF + 8 * (s0 + (q) + 1), 0);                           \
                        _Pragma("unroll") for (int k = 0; k < 4; k++) ldsm4(&a[((q) + 1) & 1][4 * k], x ^ (k * 32)); \
                        if (((q) == 8 || (q) == 9) && s0 == 0) {                                     \
                            const uint32_t ld0 = sb + SCR0 + w * 8192 + (32 * wg + mm) * 128 + ((rr ^ mm) << 4); \
                            if ((q) == 8) mbar_wait(bar + 8 * B_GD, 0);                              \
                            _Pragma("unroll") for (int k = 4 * ((q) & 1); k < 4 * ((q) & 1) + 4; k++) \
                                ldsm4t(&h0c[4 * k], (ld0 ^ ((k & 1) << 6)) + k * 512);               \
                        }                                                                            \
                        const uint32_t ok = mbar_test(bF + 8 * jn, nph);                             \
                        if (AEPOS == 1) {                                                            \
                            const uint32_t* an = a[((q) + 1) & 1];                                   \
                            if (el) mbar_arrive(bar + 8 * (B_AE + jn) + ((an[1] | an[5] | an[9] | an[13]) & zr)); \
                        }                                                                            \
                        wg_wait<0>();                                                                \
                        if (el) mbar_arrive(bF + 8 * (B_W1E - B_W1F + j));                           \
                        if (el0) mbar_expect(bF + 8 * j, 16384);                                     \
                        if (AEPOS == 0) {                                                                        \
                            const uint32_t* an = a[((q) + 1) & 1];                                   \
                            if (el) mbar_arrive(bar + 8 * (B_AE + jn) + ((an[1] | an[5] | an[9] | an[13]) & zr)); \
                        }                                                                            \
                        if (((q) == 11 || (q) == 12) && el) mbar_arrive(bar + 8 * (B_FR0 + ((q) == 12))); \
                        if ((q) == 7) { P1_ST0(6) __syncwarp(); if (el) mbar_arrive(bar + 8 * B_GD); } \
                        if (!ok) mbar_wait(bF + 8 * jn, nph);                                        \
                        asm volatile("bar.sync %0, 256;" ::"r"(bid) : "memory");                     \
                        if (tid0 && ((q) & 1)) STAMP(8 + ((s0 + (q)) >> 1));                         \
                    }
                do {
                    constexpr int s0 = 0;
                    P1_STEP(0) P1_STEP(1) P1_STEP(2) P1_STEP(3) P1_STEP(4) P1_STEP(5) P1_STEP(6) P1_STEP(7)
                } while (0);
#pragma unroll
                for (int k = 0; k < 32; k++) h0c[k] = 0;
#pragma unroll 1
                for (int s0 = 0; s0 < 18; s0 += 6) {
                    P1_STEP(8) P1_STEP(9) P1_STEP(10) P1_STEP(11) P1_STEP(12) P1_STEP(13)
                }
#undef P1_STEP
                if (!wg) asm volatile("bar.sync 2, 256;" ::: "memory");
            }
            asm volatile("barrier.cluster.wait.aligned;" ::: "memory");
            const uint32_t remb = mapa(sb, c ^ 1);
            wg_wait<0>();
            fence_regs<64>(d); fence_regs<8>(zacc);
            if (el) { mbar_arrive(bar + 8 * B_FR2); arrive_cluster(remb + OFF_BAR + 8 * B_RDY + 8 * wg); }
            if (tid0) STAMP(30);
            const uint32_t xo = OFF_SCR + wg * 20480 + (tid & 127) * 16;
            uint32_t xm[20];
#pragma unroll
            for (int k = 0; k < 16; k++) xm[k] = pack_bf16(d[4 * k + 2], d[4 * k + 3]);
            xm[16] = __float_as_uint(zacc[2]); xm[17] = __float_as_uint(zacc[3]); xm[18] = __float_as_uint(zacc[6]); xm[19] = __float_as_uint(zacc[7]);
            const uint32_t stb = sb + OFF_SCR + (2 * wg) * 8192 + (16 * w + 8 * (mm & 1) + rr) * 128 + (((mm >> 1) ^ rr) << 4);
            const uint32_t ldb = sb + OFF_SCR + w * 8192 + (32 * wg + mm) * 128 + ((rr ^ mm) << 4);
            float e0 = 0.f, e1 = 0.f;
            if (SPOS == 1) {
            mbar_wait(bar + 8 * B_RDY + 8 * wg, 0);
            if (tid0) STAMP(31);
#pragma unroll
            for (int k = 0; k < 5; k++)
                asm volatile("st.async.shared::cluster.mbarrier::complete_tx::bytes.v4.b32 [%0],{%1,%2,%3,%4},[%5];"
                             ::"r"(remb + xo + k * 2048), "r"(xm[4 * k]), "r"(xm[4 * k + 1]), "r"(xm[4 * k + 2]), "r"(xm[4 * k + 3]),
                             "r"(remb + OFF_BAR + 8 * B_HX + 8 * wg) : "memory");
            }
            fence_acq_async();
            wg_fence();
            half64<true, 0, OFF_L + 8 * S_TILE>(accA, wf + 16, cb);
            half64<true, 1, OFF_L + 8 * S_TILE>(accB, wf + 16, cb);
            wg_commit();
            if (SPOS == 0) {
            mbar_wait(bar + 8 * B_RDY + 8 * wg, 0);
            if (tid0) STAMP(31);
#pragma unroll
            for (int k = 0; k < 5; k++)
                asm volatile("st.async.shared::cluster.mbarrier::complete_tx::bytes.v4.b32 [%0],{%1,%2,%3,%4},[%5];"
                             ::"r"(remb + xo + k * 2048), "r"(xm[4 * k]), "r"(xm[4 * k + 1]), "r"(xm[4 * k + 2]), "r"(xm[4 * k + 3]),
                             "r"(remb + OFF_BAR + 8 * B_HX + 8 * wg) : "memory");
            }
            mbar_wait(bar + 8 * (B_RF + 1), 0);
            fence_acq_async();
            wg_fence();
            half64<false, 0, OFF_B>(accA, wf, cb);
            wg_commit();
            if (tid0) STAMP(32);
#define GELU8(K0)                                                                                           \
            _Pragma("unroll") for (int k = (K0); k < (K0) + 8; k++) {                                       \
                const uint32_t hr = xm[k], w2 = *(const uint32_t*)(sm + OFF_W2 + wg * 256 + t * 4 + k * 16);                                           \
                const float x0 = d[4 * k] + bf_lo(hr), x1 = d[4 * k + 1] + bf_hi(hr);                       \
                const float t0 = tanh_fast(x0 * fmaf(x0 * x0, 0.035677408136300125f, 0.7978845608028654f)); \
                const float t1 = tanh_fast(x1 * fmaf(x1 * x1, 0.035677408136300125f, 0.7978845608028654f)); \
                e0 = fmaf(fmaf(x0, t0, x0), bf_lo(w2), e0);                                             \
                e1 = fmaf(fmaf(x1, t1, x1), bf_hi(w2), e1);                                             \
            }
            float c1[8], c2[16];
#define DEEP_OUT                                                                                            \
            {                                                                                               \
                GELU8(0)                                                                                    \
                GELU8(8)                                                                                    \
                float deep = 0.5f * (e0 + e1);                                                              \
                deep += __shfl_xor_sync(0xffffffffu, deep, 1);                                              \
                deep += __shfl_xor_sync(0xffffffffu, deep, 2);                                              \
                if (t == 0) sts32(sb + OFF_RED + 256 + (tid >> 2) * 4, __float_as_uint(deep));              \
            }
#define H0_0                                                                                                \
            {                                                                                               \
                mbar_wait(bar + 8 * B_PREP, 0);                                                             \
                mbar_wait(bar + 8 * B_SEF, 0);                                                              \
                mbar_wait_cluster(bar + 8 * B_HX + 8 * wg, 0);                                                       \
                if (tid0) STAMP(33);                                                                        \
                _Pragma("unroll") for (int k = 4; k >= 0; k--) lds128(xm + 4 * k, sb + xo + k * 2048); \
                const uint32_t z0 = pack_bf16((zacc[0] + __uint_as_float(xm[16])) * (1.f / 128.f), (zacc[1] + __uint_as_float(xm[17])) * (1.f / 128.f)); \
                const uint32_t z1 = pack_bf16((zacc[4] + __uint_as_float(xm[18])) * (1.f / 128.f), (zacc[5] + __uint_as_float(xm[19])) * (1.f / 128.f)); \
                asm volatile("st.shared.v2.u32 [%0],{%1,%2};" ::"r"(sb + OFF_PIDX + tid * 8), "r"(z0), "r"(z1) : "memory"); \
                __syncwarp();                                                                               \
                if (el) mbar_arrive(bar + 8 * B_SB);         \
                if (GPOS == 1) DEEP_OUT                                                                     \
            }
#define H0_1                                                                                                \
            {                                                                                               \
                uint32_t y[4];                                                                              \
                asm volatile("ld.shared.v2.u32 {%0,%1},[%2];" : "=r"(y[0]), "=r"(y[1]) : "r"(sb + OFF_PIDX + (tid & 127) * 8) : "memory"); \
                asm volatile("ld.shared.v2.u32 {%0,%1},[%2];" : "=r"(y[2]), "=r"(y[3]) : "r"(sb + OFF_PIDX + 1024 + (tid & 127) * 8) : "memory"); \
                const uint32_t za0 = vprmt(y[0], y[2], 0x5410), za1 = vprmt(y[0], y[2], 0x7632);            \
                const uint32_t za2 = vprmt(y[1], y[3], 0x5410), za3 = vprmt(y[1], y[3], 0x7632);            \
                wg_fence();                                                                                 \
                wg16<false, (128 >> 4)>(c1, za0, za0, za1, za1, (sbm + (OFF_SE >> 4)) | ((256 >> 4) << 16)); \
                wg16<true, (128 >> 4)>(c1, za2, za2, za3, za3, (sbm + ((OFF_SE + 512) >> 4)) | ((256 >> 4) << 16)); \
                wg_commit();                                                                                \
            }
#define H0_2                                                                                                \
            {                                                                                               \
                fence_regs<8>(c1);                                                                          \
                uint32_t a2[4];                                                                             \
                _Pragma("unroll") for (int q = 0; q < 2; q++) {                                             \
                    const uint32_t xx = pack_bf16(c1[4 * q], c1[4 * q + 1]);                                \
                    const float x0 = bf_lo(xx), x1 = bf_hi(xx);               \
                    const float y0 = x0 * rcpf(1.f + ex2f(x0 * fmaf(x0 * x0, -0.10294324f, -2.30220819f))); \
                    const float y1 = x1 * rcpf(1.f + ex2f(x1 * fmaf(x1 * x1, -0.10294324f, -2.30220819f))); \
                    a2[2 * q] = a2[2 * q + 1] = vpack(y0, y1);                                              \
                }                                                                                           \
                wg_fence();                                                                                 \
                wg32<false, ((OFF_SE + 1024) >> 4) | ((512 >> 4) << 16), (128 >> 4)>(c2, a2, sbm);          \
                wg_commit();                                                                                \
                if (GPOS == 0) DEEP_OUT                                                                     \
            }
#define H0_P                                                                                                \
            {                                                                                               \
                const uint32_t zero = lds32(sb + OFF_SEL);                                                  \
                _Pragma("unroll") for (int k = 0; k < 32; k++) H[0][k] = vxor(h0c[k], zero);                \
            }
#define H0_3                                                                                                \
            {                                                                                               \
                wg_wait<0>();                                                                               \
                fence_regs<16>(c2);                                                                         \
                _Pragma("unroll") for (int nt = 0; nt < 4; nt++) {                                          \
                    const uint32_t xx = pack_bf16(c2[4 * nt], c2[4 * nt + 1]);                              \
                    ai[nt] = vpack(rcpf(1.f + ex2f(bf_lo(xx) * -1.4426950408889634f)), rcpf(1.f + ex2f(bf_hi(xx) * -1.4426950408889634f))); \
                }                                                                                           \
                ai[3] = __shfl_sync(0xffffffffu, ai[3], lane & 28);                                         \
            }
            EW_STEP(0, 1, 2, OFF_B, 0, OFF_A, OFF_L + 16 * S_TILE, H0_P, H0_0, H0_1, H0_2, H0_3)
        }

        float s0 = 0.f, s1 = 0.f;
#pragma unroll 1
        for (int wave = 0;; wave++) {
            {
                const int tid2 = tid_again();
                const int w = (tid2 >> 5) & 3, mm = (tid2 >> 3) & 3, rr = tid2 & 7, g = (tid2 >> 2) & 7, t = tid2 & 3;
                const bool tid0 = (tid2 == 0);
                const uint32_t PB0 = wave ? OFF_A : OFF_L, PD2 = wave ? OFF_L - OFF_A : 16 * S_TILE, PB3 = wave ? OFF_X : OFF_L + 24 * S_TILE;
                const uint32_t FB1 = wave ? OFF_L + 8 * S_TILE : OFF_B, FB2 = wave ? OFF_L + 16 * S_TILE : OFF_A, FB3 = wave ? OFF_L + 24 * S_TILE : OFF_X;
                {
                    const uint32_t stb = sb + OFF_SCR + (2 * wg) * 8192 + (16 * w + 8 * (mm & 1) + rr) * 128 + (((mm >> 1) ^ rr) << 4);
                    const uint32_t ldb = sb + OFF_SCR + w * 8192 + (32 * wg + mm) * 128 + ((rr ^ mm) << 4);
                    EW_STEP(wave, 2, BE, FB2, PB0 + PD2, FB3, PB3, , , , , )
                }
                const uint32_t zero = lds32(sb + OFF_SEL);
                const uint32_t row = sb + (8 * w + g) * 128;
                const uint32_t pb0 = swz(row + PB0 + (2 * t) * S_TILE) ^ (64 * wg);
                const uint32_t pb1 = swz(row + PB0 + (2 * t + 1) * S_TILE) ^ (64 * wg);
                const uint32_t pb6 = (t < 2) ? swz(row + PB3 + t * S_TILE) ^ (64 * wg) : sb + OFF_ZERO;
                const uint32_t jaddr = (rr < 2) ? sb + FB1 + REL_JIT + w * 2048 + (32 * wg + (mm & 1)) * 32 + rr * 16 : sb + OFF_ZERO;
                uint32_t pr[2][7][4];
#define T_PARTQ(b, q) lds128(pr[(b) & 1][q], (((q) == 6 ? pb6 : ((q) & 1) ? pb1 : pb0) ^ ((b) << 4)) + ((q) == 6 || (q) < 2 ? 0u : (q) < 4 ? 8 * S_TILE : PD2));
                wg_wait<0>();
                fence_regs<16>(accA);
                {
                    const uint32_t jb = sb + FB1 + REL_JIT + (mm >> 1) * 2048 + (16 * w + 8 * (mm & 1) + rr) * 32 + wg * 16;
                    stsm4(jb, pack_bf16(accA[0], accA[1]), pack_bf16(accA[2], accA[3]), pack_bf16(accA[4], accA[5]), pack_bf16(accA[6], accA[7]));
                    stsm4(jb + 4096, pack_bf16(accA[8], accA[9]), pack_bf16(accA[10], accA[11]), pack_bf16(accA[12], accA[13]), pack_bf16(accA[14], accA[15]));
                }
                float aj[7];
#pragma unroll
                for (int q = 0; q < 3; q++) { aj[2 * q] = bf_lo(ai[q] ^ zero); aj[2 * q + 1] = bf_hi(ai[q] ^ zero); }
                aj[6] = (t & 1) ? bf_hi(ai[3]) : bf_lo(ai[3]);
                const uint32_t meta = 0xEEEE4444u ^ zero;
                mbar_wait(bar + 32 * wg + 8 * B_WCF, 0);
                asm volatile("bar.sync 1, 256;" ::: "memory");
                if (tid0) STAMP(36 + wave * 8 + 3);
                constexpr uint32_t ring = (WC_LBO >> 4) << 16;
                const uint32_t rb = sbm + wg * (WC_STAGE >> 4) + (FB1 >> 4);
                const uint32_t bw = bar + 32 * wg;
                float tp[2][16], tq[2][16];
                uint32_t jj[2][2], hh[2][2], v[2][8];
#define T_JIT(k) ldsm2t(jj[(k) & 1][0], jj[(k) & 1][1], jaddr + (k) * 64);
#define T_PREP(k)                                                                                   \
                {                                                                                   \
                    uint32_t* vv = v[(k) & 1];                                                      \
                    vv[0] = mul_bf16x2(H[0][2 * (k)], ai[0]); vv[1] = mul_bf16x2(H[0][2 * (k) + 1], ai[0]); \
                    vv[2] = mul_bf16x2(H[1][2 * (k)], ai[1]); vv[3] = mul_bf16x2(H[1][2 * (k) + 1], ai[1]); \
                    vv[4] = mul_bf16x2(H[2][2 * (k)], ai[2]); vv[5] = mul_bf16x2(H[2][2 * (k) + 1], ai[2]); \
                    hh[(k) & 1][0] = vxor(H[2][2 * (k)], zero); hh[(k) & 1][1] = vxor(H[2][2 * (k) + 1], zero); \
                    vv[6] = mul_bf16x2(jj[(k) & 1][0], ai[3]); vv[7] = mul_bf16x2(jj[(k) & 1][1], ai[3]); \
                }
#define T_ISSUE(k)                                                                                  \
                {                                                                                   \
                    constexpr uint32_t lo = ring + (wc_slot((k) & 3) >> 4);                 \
                    constexpr int n0 = 4 * ((k) & 3);                                               \
                    const uint32_t* vv = v[(k) & 1];                                                \
                    wg_fence();                                                                     \
                    wgsp32<false, (n0 < DHI), lo>(tp[(k) & 1], H[0][2 * (k)], H[0][2 * (k) + 1], H[1][2 * (k)], H[1][2 * (k) + 1], rb, meta); \
                    wgsp32<false, (n0 + 1 < DHI), lo + (WC_TILE >> 4)>(tq[(k) & 1], vv[0], vv[1], vv[2], vv[3], rb, meta); \
                    wgsp32<true, (n0 + 2 < DHI), lo + (4 * WC_LBO >> 4)>(tp[(k) & 1], hh[(k) & 1][0], hh[(k) & 1][1], jj[(k) & 1][0], jj[(k) & 1][1], rb, meta); \
                    wgsp32<true, (n0 + 3 < DHI), lo + ((WC_TILE + 4 * WC_LBO) >> 4)>(tq[(k) & 1], vv[4], vv[5], vv[6], vv[7], rb, meta); \
                    wg_commit();                                                                    \
                }
#define T_FMA(p)                                                                                    \
                {                                                                                   \
                    const float* P = tp[(p) & 1];                                                   \
                    const float* Q = tq[(p) & 1];                                                   \
                    if (DOTMODE == 0) {                                                             \
                        _Pragma("unroll") for (int q = 0; q < 7; q++) {                             \
                            const int di = 4 * (q >> 1) + (q & 1);                                  \
                            const uint32_t x = pr[((p) >> 2) & 1][q][(p) & 3];                                      \
                            s0 = fmaf(bf_lo(x), fmaf(aj[q], Q[di], P[di]), s0);                     \
                            s1 = fmaf(bf_hi(x), fmaf(aj[q], Q[di + 2], P[di + 2]), s1);             \
                        }                                                                           \
                    } else {                                                                        \
                        uint32_t acc2 = 0;                                                          \
                        _Pragma("unroll") for (int q = 0; q < 7; q++) {                             \
                            const int di = 4 * (q >> 1) + (q & 1);                                  \
                            acc2 = fma_bf16x2(pr[((p) >> 2) & 1][q][(p) & 3], pack_bf16(fmaf(aj[q], Q[di], P[di]), fmaf(aj[q], Q[di + 2], P[di + 2])), acc2); \
                        }                                                                           \
                        s0 += bf_lo(acc2); s1 += bf_hi(acc2);                                       \
                    }                                                                               \
                    asm volatile("" : "+f"(s0), "+f"(s1));                                          \
                    if ((p) < 12) {      \
                        constexpr int nb = ((p) >> 2) + 1, ph = (p) & 3;                            \
                        if (nb == 1 && PSPREAD < 2) {                                               \
                            if (ph == 3) { T_PARTQ(nb, 0) T_PARTQ(nb, 1) T_PARTQ(nb, 2) T_PARTQ(nb, 3) T_PARTQ(nb, 4) T_PARTQ(nb, 5) T_PARTQ(nb, 6) } \
                        } else if (nb == 1) {                                                       \
                            if (ph == 2) { T_PARTQ(nb, 0) T_PARTQ(nb, 1) T_PARTQ(nb, 2) }           \
                            if (ph == 3) { T_PARTQ(nb, 3) T_PARTQ(nb, 4) T_PARTQ(nb, 5) T_PARTQ(nb, 6) } \
                        } else {                                                                    \
                            if (ph == 0) { T_PARTQ(nb, 0) }                                         \
                            if (ph == 1) { T_PARTQ(nb, 1) T_PARTQ(nb, 2) }                          \
                            if (ph == 2) { T_PARTQ(nb, 3) T_PARTQ(nb, 4) }                          \
                            if (ph == 3) { T_PARTQ(nb, 5) T_PARTQ(nb, 6) }                          \
                        }                                                                           \
                    }                                                                               \
                }
#define T_DONE(k)                                                                                   \
                {                                                                                   \
                    fence_regs<16>(tp[(k) & 1]); fence_regs<16>(tq[(k) & 1]);                       \
                    if ((k) < 12) { if (el) mbar_arrive2(bw + 8 * (B_WCE + ((k) & 3))); }           \
                    else if (el) mbar_arrive(bar + 8 * (B_TD + (k) - 12));        \
                }
#define T_STEP(k)                                                                                   \
                {                                                                                   \
                    constexpr int kn = ((k) < 15) ? (k) + 1 : 15, kp = ((k) > 0) ? (k) - 1 : 0;     \
                    if (TWAIT == 0) mbar_wait_pre(bw + 8 * (B_WCF + ((k) & 3)), ((k) >> 2) & 1, ok); \
                    if (TWAIT == 1) { if (!ok) mbar_wait(bw + 8 * (B_WCF + ((k) & 3)), ((k) >> 2) & 1); } \
                    if (TWAIT == 2) mbar_wait(bw + 8 * (B_WCF + ((k) & 3)), ((k) >> 2) & 1);       \
                    T_ISSUE(k)                                                                      \
                    if ((k) > 0) { wg_wait<1>(); T_DONE(kp) }                                       \
                    if ((k) < 15) {                                                                 \
                        T_JIT(kn)                                                                   \
                        if (TWAIT < 2) ok = mbar_test(bw + 8 * (B_WCF + (kn & 3)), (kn >> 2) & 1); \
                    }                                                                               \
                    if ((k) > 0) T_FMA(kp)                                                          \
                    if (WFPOS == 0 && (k) >= 10 && (k) <= 13) {   \
                        constexpr int u = ((k) - 10) & 3;                                           \
                        ldg128(wf + 4 * u, wsrc2 + c * 8192 + u * 2048);                            \
                        ldg128(wf + 16 + 4 * u, wsrc2 + (c ^ 1) * 8192 + u * 2048);                 \
                    }                                                                               \
                    if (WFPOS && ((k) == WFPOS || (k) == WFPOS + 1)) {                              \
                        constexpr int u = ((k) - WFPOS) & 1;                                        \
                        _Pragma("unroll") for (int i = 0; i < 4; i++) ldg128(wf + 16 * u + 4 * i, wsrc2 + (c ^ u) * 8192 + i * 2048); \
                    }                                                                               \
                    if ((k) < 15) T_PREP(kn)                                                        \
                }
                uint32_t ok = 0;
                const char* wsrc2 = (const char*)g_wt + ((c ^ 1) * 16384 + (tid2 & 127) * 16);
                {
                    const uint32_t ldb = sb + OFF_SCR + w * 8192 + (32 * wg + mm) * 128 + ((rr ^ mm) << 4);
                    T_JIT(0)
                    ldsm4t(&H[2][0], ldb);
                    T_JIT(1)
                    ok = mbar_test(bw + 8 * (B_WCF + 1), 0);
#pragma unroll
                    for (int k = 1; k < 8; k++) ldsm4t(&H[2][4 * k], (ldb ^ ((k & 1) << 6)) + k * 512);
                    if (el) mbar_arrive(bar + 8 * B_SB);
                    T_PREP(0)
                    if (RELPOS == 1) T_ISSUE(0)
                    WC_RELEASE2(2, wave == 0, ((H[2][4] | H[2][8] | H[2][12]) | (H[2][16] | H[2][20] | H[2][24]) | H[2][28] | H[2][0]) & zero)
                    if (RELPOS == 0) T_ISSUE(0)
                    T_PARTQ(0, 0) T_PARTQ(0, 1) T_PARTQ(0, 2) T_PARTQ(0, 3) T_PARTQ(0, 4) T_PARTQ(0, 5) T_PARTQ(0, 6)
                    T_PREP(1)
                }
                T_STEP(1) T_STEP(2) T_STEP(3) T_STEP(4) T_STEP(5) T_STEP(6) T_STEP(7)
                T_STEP(8) T_STEP(9) T_STEP(10) T_STEP(11) T_STEP(12) T_STEP(13) T_STEP(14)
                mbar_wait_pre(bw + 8 * (B_WCF + 3), 1, ok);
                T_ISSUE(15)
                wg_wait<1>();
                T_DONE(14)
                wg_fence();
                half64<true, 0, OFF_L>(accA, wf, cb);
                wg_commit();
                T_FMA(14)
                wg_wait<1>();
                T_DONE(15)
                if (GV == 2) { wg_fence(); half64<true, 1, OFF_L>(accB, wf, cb); wg_commit(); }
                T_FMA(15)
                if (tid0) STAMP(40 + 8 * wave);
            }
            if (wave) break;
            if (GV == 1) { wg_fence(); half64<true, 1, OFF_L>(accB, wf, cb); wg_commit(); }
            {
                const int tid2 = tid_again();
                const int w = (tid2 >> 5) & 3, mm = (tid2 >> 3) & 3, rr = tid2 & 7;
                const bool tid0 = (tid2 == 0);
                const uint32_t stb = sb + OFF_SCR + (2 * wg) * 8192 + (16 * w + 8 * (mm & 1) + rr) * 128 + (((mm >> 1) ^ rr) << 4);
                const uint32_t ldb = sb + OFF_SCR + w * 8192 + (32 * wg + mm) * 128 + ((rr ^ mm) << 4);
                mbar_wait(bar + 8 * (B_RF + 4), 0);
                fence_acq_async();
                wg_fence();
                half64<false, 0, OFF_A>(accA, wf + 16, cb);
                wg_commit();
                wg_wait<1>();
                if (el) mbar_arrive(bar + 8 * (B_GD + 4));
                EW_STEP(1, 0, 1, 0, OFF_A, OFF_L + 8 * S_TILE, OFF_B, , , , , )
                EW_STEP(1, 1, 0, OFF_L + 8 * S_TILE, OFF_B, OFF_L + 16 * S_TILE, OFF_L, , , , , )
                if (BE) wg_wait<0>();
            }
        }
        float logit = s0 + s1;
        logit += __shfl_xor_sync(0xffffffffu, logit, 1);
        logit += __shfl_xor_sync(0xffffffffu, logit, 2);
        float* red = (float*)(sm + OFF_RED);
        const int tid3 = tid_again();
        if ((tid3 & 3) == 0) red[tid3 >> 2] = logit;
        asm volatile("bar.sync 1, 256;" ::: "memory");
        if (tid3 < 32) out[own0 + tid3] = __float2bfloat16_rn(bfr(red[tid3] + red[32 + tid3]) + bfr(red[64 + tid3] + red[96 + tid3]));
        wg_wait<0>();
        if (tid3 == 0) STAMP(60);
    }
}

extern "C" void kernel_launch(void* const* d_in, const int* in_sizes, int n_in, void* d_out, int out_size) {
    static CUtensorMap tm;
    static const void* tm_ptr = nullptr;
    if (tm_ptr != d_in[6]) {
        void* fn = nullptr;
        cudaDriverEntryPointQueryResult qr;
        cudaGetDriverEntryPoint("cuTensorMapEncodeTiled", &fn, cudaEnableDefault, &qr);
        typedef CUresult (*PFN)(CUtensorMap*, CUtensorMapDataType, cuuint32_t, void*, const cuuint64_t*, const cuuint64_t*,
                                const cuuint32_t*, const cuuint32_t*, CUtensorMapInterleave, CUtensorMapSwizzle,
                                CUtensorMapL2promotion, CUtensorMapFloatOOBfill);
        cuuint64_t gd[3] = {64, 3328, 4};
        cuuint64_t gs[2] = {512, 128};
        cuuint32_t bd[3] = {64, 64, 2};
        cuuint32_t es[3] = {1, 1, 1};
        ((PFN)fn)(&tm, CU_TENSOR_MAP_DATA_TYPE_BFLOAT16, 3, d_in[6], gd, gs, bd, es, CU_TENSOR_MAP_INTERLEAVE_NONE,
                  CU_TENSOR_MAP_SWIZZLE_128B, CU_TENSOR_MAP_L2_PROMOTION_L2_256B, CU_TENSOR_MAP_FLOAT_OOB_FILL_NONE);
        cudaFuncSetAttribute(fib_kernel, cudaFuncAttributeMaxDynamicSharedMemorySize, SMEM_BYTES);
        tm_ptr = d_in[6];
    }
    fib_kernel<<<128, 384, SMEM_BYTES, cudaStreamPerThread>>>(
        (const int*)d_in[0], (const char*)d_in[1], (const char*)d_in[5], (const char*)d_in[6], (const unsigned short*)d_in[4],
        (const __nv_bfloat16*)d_in[7], tm, (const unsigned short*)d_in[2], (const unsigned short*)d_in[3], (__nv_bfloat16*)d_out);
}
```
